```python
import torch

def _softmax(x, axis=-1):
    return torch.softmax(x, dim=axis)
def _gelu(x):
    return torch.nn.functional.gelu(x, approximate="tanh")
def _silu(x):
    return torch.nn.functional.silu(x)
def _sigmoid(x):
    return torch.sigmoid(x)
def _layernorm(x, axis=-1, eps=1e-5):
    m = x.mean(dim=axis, keepdim=True)
    v = x.var(dim=axis, keepdim=True, unbiased=False)
    return (x - m) / torch.sqrt(v + eps)
def _scatter_add(tgt, idx, src, axis=0):
    return tgt.clone().index_add_(axis, idx, src)
def _segment_sum(src, seg, n):
    out = torch.zeros((n,) + src.shape[1:], dtype=src.dtype)
    return out.index_add_(0, seg, src)
def _pad(x, pw):
    flat = tuple(v for pair in reversed(pw) for v in pair)
    return torch.nn.functional.pad(x, flat)

kernel_name = 'standalone__kernel_systems_refs_featgraph__graph'

def setup_inputs():

    _w = (lambda a: (lambda t: t.to(torch.bfloat16) if t.is_floating_point() else t)(torch.as_tensor(a)))
    N, deg, D = 10000, 16, 128
    E = N * deg
    scale = D ** -0.5
    src = (lambda lo, hi, *s: torch.randint(lo, hi, s))(0, N, E).to(torch.int64)
    dst = (lambda lo, hi, *s: torch.randint(lo, hi, s))(0, N, E).to(torch.int64)
    return {
        "x": _w((lambda *s: torch.randn(*s, dtype=torch.bfloat16) * 0.8)(N, D)),
        "src": _w(src),
        "dst": _w(dst),
        "w_q": _w((lambda *s: torch.randn(*s, dtype=torch.bfloat16) * 0.8)(D, D) * scale),
        "w_v": _w((lambda *s: torch.randn(*s, dtype=torch.bfloat16) * 0.05)(D, D) * scale),
    }

def reference(x, src, dst, w_q, w_v):
    N, D = x.shape
    xs = x[src]
    xd = x[dst]
    q = xd @ w_q
    logits = torch.einsum('ed,ed->e', xs, q) * (float(D) ** -0.5)
    alpha = _sigmoid(logits)
    msg = alpha[:, None] * (xs @ w_v)
    return _segment_sum(msg, dst, N)
```

```cpp
#include <cuda_runtime.h>
#include <cuda_bf16.h>
#include <cuda.h>
#include <stdint.h>

namespace fg {

constexpr int N_NODES = 10000;
constexpr int N_EDGES = 160000;
constexpr int NCTA    = 132;
constexpr int TILE    = 76;
constexpr int NGRP    = 19;
constexpr int NTHR    = 640;
constexpr int SLICE   = 1216;
constexpr int BOXCAP  = 24;
constexpr int BOXPITCH = 28;
constexpr int SUBCAP  = 64;
constexpr int FLATCAP = 128;
constexpr int POLL_LIMIT = 200;
#define T_POLL 2600
#define T_X 400
#define T_WQ 1500
#define T_WV 3000
#define PREWRITE 1

constexpr uint32_t SB     = 1024;
constexpr uint32_t SM_WQ   = SB;
constexpr uint32_t SM_WV   = SM_WQ + 32768;
constexpr uint32_t SM_T    = SM_WV + 32768;
constexpr uint32_t SM_SUB  = SM_T + 20480;
constexpr uint32_t SM_BOX  = SM_SUB + 128 * SUBCAP * 2;
constexpr uint32_t SM_FLAT = SM_BOX + NCTA * BOXPITCH * 4;
constexpr uint32_t FLATPITCH = (FLATCAP + 32) * 2;
constexpr uint32_t SM_CNT  = SM_FLAT + 20 * FLATPITCH;
constexpr uint32_t SM_LCNT = SM_CNT + 528;
constexpr uint32_t SM_MISC = SM_LCNT + 512;
constexpr uint32_t SM_MBQ  = SM_MISC + 16;
constexpr uint32_t SM_MBV  = SM_MISC + 24;
constexpr uint32_t SM_RESC = SM_MISC + 32;
constexpr uint32_t SM_END  = SM_RESC + NCTA * 4;
constexpr int SM_TOTAL = SM_END - SB;

struct Scratch {
    uint4 mail[NCTA * NCTA * 4];
    unsigned epoch[NCTA];
};
__device__ __align__(128) Scratch g_scratch;
#define TS(i)
#define TS_INIT()
#define TS_DUMP()
constexpr int SM_ALLOC = SM_TOTAL;

__device__ __forceinline__ uint32_t movm(uint32_t a) {
    uint32_t d; asm volatile("movmatrix.sync.aligned.m8n8.trans.b16 %0, %1;" : "=r"(d) : "r"(a)); return d;
}
__device__ __forceinline__ void mma(float (&c)[4], uint32_t a0, uint32_t a1, uint32_t a2, uint32_t a3, uint32_t b0, uint32_t b1) {
    asm volatile("mma.sync.aligned.m16n8k16.row.col.f32.bf16.bf16.f32 {%0,%1,%2,%3}, {%4,%5,%6,%7}, {%8,%9}, {%0,%1,%2,%3};"
                 : "+f"(c[0]), "+f"(c[1]), "+f"(c[2]), "+f"(c[3]) : "r"(a0), "r"(a1), "r"(a2), "r"(a3), "r"(b0), "r"(b1));
}
__device__ __forceinline__ void ldgp(uint4& v, const void* p, bool pred) {
    asm volatile("{\n.reg .pred p;\nsetp.ne.u32 p, %5, 0;\n@p ld.global.nc.v4.u32 {%0,%1,%2,%3}, [%4];\n}"
                 : "+r"(v.x), "+r"(v.y), "+r"(v.z), "+r"(v.w) : "l"(p), "r"((uint32_t)pred) : "memory");
}
__device__ __forceinline__ uint4 lds128(uint32_t a) {
    uint4 v; asm volatile("ld.shared.v4.u32 {%0,%1,%2,%3}, [%4];" : "=r"(v.x), "=r"(v.y), "=r"(v.z), "=r"(v.w) : "r"(a) : "memory"); return v;
}
__device__ __forceinline__ uint32_t lds32(uint32_t a) { uint32_t v; asm volatile("ld.shared.u32 %0, [%1];" : "=r"(v) : "r"(a) : "memory"); return v; }
__device__ __forceinline__ uint32_t lds16(uint32_t a) { uint16_t v; asm volatile("ld.shared.u16 %0, [%1];" : "=h"(v) : "r"(a) : "memory"); return v; }
__device__ __forceinline__ void sts32(uint32_t a, uint32_t v) { asm volatile("st.shared.u32 [%0], %1;" :: "r"(a), "r"(v) : "memory"); }
__device__ __forceinline__ void sts16(uint32_t a, uint32_t v) { asm volatile("st.shared.u16 [%0], %1;" :: "r"(a), "h"((uint16_t)v) : "memory"); }
__device__ __forceinline__ uint32_t atoms_inc(uint32_t a) { uint32_t r; asm volatile("atom.shared.add.u32 %0, [%1], 1;" : "=r"(r) : "r"(a) : "memory"); return r; }
__device__ __forceinline__ void sts128(uint32_t a, uint32_t x, uint32_t y, uint32_t z, uint32_t w) {
    asm volatile("st.shared.v4.u32 [%0], {%1,%2,%3,%4};" :: "r"(a), "r"(x), "r"(y), "r"(z), "r"(w) : "memory");
}
__device__ __forceinline__ void bar_sync(int id, int n)   { asm volatile("bar.sync %0, %1;" :: "r"(id), "r"(n) : "memory"); }
__device__ __forceinline__ void bar_arrive(int id, int n) { asm volatile("bar.arrive %0, %1;" :: "r"(id), "r"(n) : "memory"); }
__device__ __forceinline__ uint32_t clock32() { uint32_t c; asm volatile("mov.u32 %0, %clock;" : "=r"(c)); return c; }
__device__ __forceinline__ void mbar_wait(uint32_t mb) {
    asm volatile("{\n.reg .pred p;\n.reg .u32 i;\nmov.u32 i, 0;\n"
                 "W: mbarrier.try_wait.parity.shared::cta.b64 p, [%0], 0;\n@p bra D;\n"
                 "add.u32 i, i, 1;\nsetp.lt.u32 p, i, 4000000;\n@p bra W;\ntrap;\nD:\n}" :: "r"(mb) : "memory");
}
__device__ __forceinline__ void tma2d(uint32_t dst, const CUtensorMap* tm, int c0, int c1, uint32_t mb) {
    asm volatile("cp.async.bulk.tensor.2d.shared::cluster.global.mbarrier::complete_tx::bytes [%0], [%1, {%2, %3}], [%4];"
                 :: "r"(dst), "l"(tm), "r"(c0), "r"(c1), "r"(mb) : "memory");
}
__device__ __forceinline__ uint32_t pack_bf16(float lo, float hi) {
    uint32_t r; asm("cvt.rn.bf16x2.f32 %0, %1, %2;" : "=r"(r) : "f"(hi), "f"(lo)); return r;
}
__device__ __forceinline__ float sigm(float s) {
    float e, r;
    asm("ex2.approx.ftz.f32 %0, %1;" : "=f"(e) : "f"(s * -0.12751743197f));
    asm("rcp.approx.ftz.f32 %0, %1;" : "=f"(r) : "f"(1.0f + e));
    return r;
}
__device__ __forceinline__ uint64_t make_desc(uint32_t addr) {
    return (uint64_t)((addr & 0x3FFFF) >> 4) | ((uint64_t)1 << 16) | ((uint64_t)64 << 32) | ((uint64_t)1 << 62);
}

__device__ __forceinline__ void tile_gemm(uint32_t sW, uint32_t sT, int warp, int lane) {
    float d[40];
    const int mh = warp >> 2;
    uint64_t da = make_desc(sW + mh * 16384), db = make_desc(sT);
    asm volatile("wgmma.fence.sync.aligned;" ::: "memory");
    #pragma unroll
    for (int s = 0; s < 8; s++) {
        uint64_t a = da + (uint64_t)(s * 128), b = db + (uint64_t)((s >> 2) * 640 + (s & 3) * 2);
        asm volatile("{\n.reg .pred p;\nsetp.ne.u32 p, %42, 0;\n"
            "wgmma.mma_async.sync.aligned.m64n80k16.f32.bf16.bf16 "
            "{%0,%1,%2,%3,%4,%5,%6,%7,%8,%9,%10,%11,%12,%13,%14,%15,%16,%17,%18,%19,"
            "%20,%21,%22,%23,%24,%25,%26,%27,%28,%29,%30,%31,%32,%33,%34,%35,%36,%37,%38,%39}, %40, %41, p, 1, 1, 1, 0;\n}"
            : "+f"(d[0]), "+f"(d[1]), "+f"(d[2]), "+f"(d[3]), "+f"(d[4]), "+f"(d[5]), "+f"(d[6]), "+f"(d[7]), "+f"(d[8]), "+f"(d[9]),
              "+f"(d[10]), "+f"(d[11]), "+f"(d[12]), "+f"(d[13]), "+f"(d[14]), "+f"(d[15]), "+f"(d[16]), "+f"(d[17]), "+f"(d[18]), "+f"(d[19]),
              "+f"(d[20]), "+f"(d[21]), "+f"(d[22]), "+f"(d[23]), "+f"(d[24]), "+f"(d[25]), "+f"(d[26]), "+f"(d[27]), "+f"(d[28]), "+f"(d[29]),
              "+f"(d[30]), "+f"(d[31]), "+f"(d[32]), "+f"(d[33]), "+f"(d[34]), "+f"(d[35]), "+f"(d[36]), "+f"(d[37]), "+f"(d[38]), "+f"(d[39])
            : "l"(a), "l"(b), "r"((uint32_t)(s != 0)) : "memory");
    }
    asm volatile("wgmma.commit_group.sync.aligned;" ::: "memory");
    asm volatile("wgmma.wait_group.sync.aligned 0;" ::: "memory");
    bar_sync(1, 256);
    const int w = warp & 3;
    const int r = lane & 7;
    uint32_t base = sT + mh * 10240 + ((lane >> 4) * 8 + r) * 128 + (((2 * w + ((lane >> 3) & 1)) ^ r) << 4);
    #pragma unroll
    for (int i = 0; i < 10; i += 2) {
        uint32_t m0 = pack_bf16(d[4 * i], d[4 * i + 1]), m1 = pack_bf16(d[4 * i + 2], d[4 * i + 3]);
        uint32_t m2 = pack_bf16(d[4 * i + 4], d[4 * i + 5]), m3 = pack_bf16(d[4 * i + 6], d[4 * i + 7]);
        asm volatile("stmatrix.sync.aligned.m8n8.x4.trans.shared.b16 [%0], {%1,%2,%3,%4};"
                     :: "r"(base + i * 1024), "r"(m0), "r"(m1), "r"(m2), "r"(m3) : "memory");
    }
}

__device__ __forceinline__ uint32_t make_entry(uint32_t s, uint32_t dl) { return s * 4 + dl + (dl >> 2) * 65532u; }
__device__ __forceinline__ void st_b128(void* p, uint32_t a, uint32_t b, uint32_t c, uint32_t d) {
    asm volatile("{\n.reg .b128 v;\n.reg .b64 lo, hi;\nmov.b64 lo, {%1,%2};\nmov.b64 hi, {%3,%4};\nmov.b128 v, {lo, hi};\n"
                 "st.relaxed.gpu.global.b128 [%0], v;\n}" :: "l"(p), "r"(a), "r"(b), "r"(c), "r"(d) : "memory");
}

__global__ void __launch_bounds__(NTHR, 1)
fg_kernel(const unsigned char* __restrict__ x, const int* __restrict__ src, const int* __restrict__ dst,
          uint4* __restrict__ out, Scratch* __restrict__ scr, int mode,
          const unsigned char* __restrict__ wq, const unsigned char* __restrict__ wv,
          const __grid_constant__ CUtensorMap tm_x, const __grid_constant__ CUtensorMap tm_wq, const __grid_constant__ CUtensorMap tm_wv) {
    extern __shared__ __align__(1024) unsigned char smem[];
    const uint32_t t_start = clock32();
    const int tid = threadIdx.x, warp = tid >> 5, lane = tid & 31;
    const int cta = blockIdx.x;
    const int g = lane >> 2, t = lane & 3;
    TS_INIT();
    TS(0);
    uint4 buf[2][4];
    int n = 0;
    bool slow = false;
    const uint32_t fl = SM_FLAT + warp * FLATPITCH;
    const uint32_t xoff = (4 * (g & 1) + t) * 16;

    if (warp == NGRP) {
        if (lane == 0 && (mode & 2)) {
            if ((uint32_t)__cvta_generic_to_shared(smem) != SB) __trap();
            asm volatile("mbarrier.init.shared::cta.b64 [%0], 1;" :: "r"(SM_MBQ) : "memory");
            asm volatile("mbarrier.init.shared::cta.b64 [%0], 1;" :: "r"(SM_MBV) : "memory");
            asm volatile("fence.mbarrier_init.release.cluster;" ::: "memory");
            asm volatile("fence.proxy.async.shared::cta;" ::: "memory");
        }
        __syncwarp();
        bar_arrive(3, NTHR);
        if (!(mode & 2)) return;
        if (lane == 0) {
            asm volatile("mbarrier.arrive.expect_tx.shared::cta.b64 _, [%0], %1;" :: "r"(SM_MBQ), "r"(20480 + 32768) : "memory");
            asm volatile("mbarrier.arrive.expect_tx.shared::cta.b64 _, [%0], %1;" :: "r"(SM_MBV), "r"(32768) : "memory");
            while (clock32() - t_start < T_X) {}
            tma2d(SM_T, &tm_x, 0, cta * TILE, SM_MBQ);
            tma2d(SM_T + 10240, &tm_x, 64, cta * TILE, SM_MBQ);
            if (cta < 128) {
                asm volatile("cp.async.bulk.prefetch.L2.global [%0], 256;" :: "l"(wq + cta * 256) : "memory");
                asm volatile("cp.async.bulk.prefetch.L2.global [%0], 256;" :: "l"(wv + cta * 256) : "memory");
            }
            while (clock32() - t_start < T_WQ) {}
            tma2d(SM_WQ, &tm_wq, 0, 0, SM_MBQ);
            tma2d(SM_WQ + 16384, &tm_wq, 64, 0, SM_MBQ);
            while (clock32() - t_start < T_WV) {}
            tma2d(SM_WV, &tm_wv, 0, 0, SM_MBV);
            tma2d(SM_WV + 16384, &tm_wv, 64, 0, SM_MBV);
        }
        __syncwarp();
    } else {
        const int e2 = cta * (SLICE / 2) + tid;
        const bool has_e = e2 < N_EDGES / 2;
        int2 d2 = make_int2(0, 0), s2 = make_int2(0, 0);
        if (has_e) { d2 = __ldg((const int2*)dst + e2); s2 = __ldg((const int2*)src + e2); }
        unsigned epoch = 0;
        if (tid == 0) epoch = __ldcg(&scr->epoch[cta]);
        const bool act = tid < NCTA * 4;
        uint4* wp = scr->mail + ((tid >> 2) * NCTA + cta) * 4 + t;
        const uint4* mp = scr->mail + cta * NCTA * 4 + tid;
        if (PREWRITE && act && (mode & 1)) st_b128(wp, 0, 0, 0, 0);
        if (tid < 132 + 128 + 1) sts32(SM_CNT + tid * 4, 0);
        {
            const uint32_t dm = (96 + ((4 * cta) & 31)) << 14;
            sts128(SM_BOX + tid * 16, dm, dm + (1 << 14), dm + (2 << 14), dm + (3 << 14));
            if (tid < NCTA * 7 - NGRP * 32) sts128(SM_BOX + (tid + NGRP * 32) * 16, dm, dm + (1 << 14), dm + (2 << 14), dm + (3 << 14));
        }
        bar_sync(2, NGRP * 32);
        #pragma unroll
        for (int s = 0; s < 2; s++)
            #pragma unroll
            for (int j = 0; j < 4; j++) buf[s][j] = lds128(SM_LCNT);
        TS(1);

        if (has_e) {
            uint32_t tl0 = __umulhi(d2.x, 56512728u), tl1 = __umulhi(d2.y, 56512728u);
            uint32_t p0 = atoms_inc(SM_CNT + tl0 * 4), p1 = atoms_inc(SM_CNT + tl1 * 4);
            sts32(SM_BOX + tl0 * (BOXPITCH * 4) + min(p0, (uint32_t)BOXCAP) * 4, make_entry(s2.x, d2.x - tl0 * TILE));
            sts32(SM_BOX + tl1 * (BOXPITCH * 4) + min(p1, (uint32_t)BOXCAP) * 4, make_entry(s2.y, d2.y - tl1 * TILE));
        }
        if (tid == 0) {
            sts32(SM_MISC + 4, (epoch & 1) << 31);
            if (mode & 2) scr->epoch[cta] = epoch + 1;
        }
        bar_sync(3, NTHR);
        TS(2);
        const uint32_t par = lds32(SM_MISC + 4);
        if (act && (mode & 1)) {
            const uint32_t bp = SM_BOX + (tid >> 2) * (BOXPITCH * 4) + t * 4;
            uint32_t c = lds32(SM_CNT + (tid >> 2) * 4);
            uint32_t e[6];
            #pragma unroll
            for (int k = 0; k < 6; k++) e[k] = lds32(bp + k * 16);
            if (__builtin_expect(c > BOXCAP, 0)) {
                #pragma unroll
                for (int k = 0; k < 6; k++) e[k] = (80 + (lane & 15)) << 14;
            }
            st_b128(wp, e[0] | (e[1] << 21), (e[1] >> 11) | (e[2] << 10) | 0x80000000u,
                        e[3] | (e[4] << 21), (e[4] >> 11) | (e[5] << 10) | par);
        }
        if (!(mode & 2)) return;
        TS(3);

        if (warp < 17) {
            const uint32_t dm = (96 + lane) << 14;
            uint32_t w0 = dm | (dm << 21), w1 = (dm >> 11) | (dm << 10), w2 = w0, w3 = w1;
            bool ok = !act;
            int it = 0;
            while (clock32() - t_start < T_POLL) {}
            do {
                if (!ok) {
                    asm volatile("{\n.reg .b128 v;\n.reg .b64 lo, hi;\nld.relaxed.gpu.global.b128 v, [%4];\nmov.b128 {lo, hi}, v;\n"
                                 "mov.b64 {%0,%1}, lo;\nmov.b64 {%2,%3}, hi;\n}" : "=r"(w0), "=r"(w1), "=r"(w2), "=r"(w3) : "l"(mp) : "memory");
                    ok = (int)(w1 & ~(w3 ^ par)) < 0;
                }
            } while (__builtin_expect(!__all_sync(0xffffffffu, ok), 0) && ++it < POLL_LIMIT);
            TS(4);
            if (__builtin_expect(__any_sync(0xffffffffu, !ok || (w0 & (0x70 << 14)) == (0x50 << 14)), 0)) {
                uint32_t bad = __ballot_sync(0xffffffffu, !ok || (w0 & (0x70 << 14)) == (0x50 << 14));
                if ((bad >> (lane & ~3)) & 0xF) {
                    w0 = dm | (dm << 21); w1 = (dm >> 11) | (dm << 10); w2 = w0; w3 = w1;
                    if (t == 0) sts32(SM_RESC + atoms_inc(SM_MISC) * 4, tid >> 2);
                }
            }
            uint32_t e[6] = {w0, __funnelshift_r(w0, w1, 21), w1 >> 10, w2, __funnelshift_r(w2, w3, 21), w3 >> 10};
            uint32_t a4[6], pos[6];
            #pragma unroll
            for (int k = 0; k < 4; k++) { a4[k] = (e[k] >> 12) & 0x1FC; pos[k] = atoms_inc(SM_LCNT + a4[k]); }
            const bool more = __any_sync(0xffffffffu, (e[4] & (0x60 << 14)) != (0x60 << 14));
            #pragma unroll
            for (int k = 0; k < 4; k++) sts16(SM_SUB + a4[k] * (SUBCAP / 2) + min(pos[k], (uint32_t)SUBCAP - 1) * 2, e[k]);
            if (__builtin_expect(more, 0)) {
                #pragma unroll
                for (int k = 4; k < 6; k++) { a4[k] = (e[k] >> 12) & 0x1FC; pos[k] = atoms_inc(SM_LCNT + a4[k]); }
                #pragma unroll
                for (int k = 4; k < 6; k++) sts16(SM_SUB + a4[k] * (SUBCAP / 2) + min(pos[k], (uint32_t)SUBCAP - 1) * 2, e[k]);
            }
        }
        bar_sync(2, NGRP * 32);
        TS(5);
        const int nres = lds32(SM_MISC);
        if (__builtin_expect(nres != 0, 0)) {
            #pragma unroll 1
            for (int k = 0; k < nres; k++) {
                int ee = lds32(SM_RESC + k * 4) * SLICE + tid;
                #pragma unroll 1
                for (int i = tid; i < SLICE && ee < N_EDGES; i += NGRP * 32, ee += NGRP * 32) {
                    uint32_t dl = (uint32_t)(__ldg(dst + ee) - cta * TILE);
                    if (dl < TILE) {
                        uint32_t e = make_entry(__ldg(src + ee), dl), a4 = (e >> 12) & 0x1FC;
                        uint32_t pos = atoms_inc(SM_LCNT + a4);
                        sts16(SM_SUB + a4 * (SUBCAP / 2) + min(pos, (uint32_t)SUBCAP - 1) * 2, e);
                    }
                }
            }
            bar_sync(2, NGRP * 32);
        }

        const uint4 c = lds128(SM_LCNT + warp * 16);
        const uint32_t p2 = c.x + c.y;
        n = p2 + c.z;
        if (__builtin_expect(max(max(c.x, c.y), c.z) > SUBCAP || n > FLATCAP, 0)) { slow = true; n = 0; }
        const uint32_t sp = SM_SUB + warp * (4 * SUBCAP * 2);
        auto fetch = [&](uint32_t f) { return lds16(sp + ((f + (f >= c.x ? SUBCAP - c.x : 0) + (f >= p2 ? SUBCAP - c.y : 0)) & (4 * SUBCAP - 1)) * 2); };
        const uint32_t v0 = fetch(lane);
        #pragma unroll
        for (int s = 0; s < 2; s++) {
            int i = 8 * s + 2 * (g >> 1);
            const unsigned char* a0 = x + (((__shfl_sync(0xffffffffu, v0, i) << 6) & 0x3FFF00) | xoff);
            const unsigned char* a1 = x + (((__shfl_sync(0xffffffffu, v0, i + 1) << 6) & 0x3FFF00) | xoff);
            ldgp(buf[s][0], a0, i < n);     ldgp(buf[s][1], a0 + 128, i < n);
            ldgp(buf[s][2], a1, i + 1 < n); ldgp(buf[s][3], a1 + 128, i + 1 < n);
        }
        TS(7);
        sts16(fl + lane * 2, v0);
        #pragma unroll
        for (int k = 1; k < FLATCAP / 32; k++) sts16(fl + (lane + 32 * k) * 2, fetch(lane + 32 * k));
        __syncwarp();
        TS(6);
    }

    auto issue = [&](int e0) {
        #pragma unroll
        for (int s = 0; s < 2; s++) {
            int i = e0 + 8 * s + 2 * (g >> 1);
            uint32_t e = lds32(fl + i * 2);
            const unsigned char* a0 = x + (((e << 6) & 0x3FFF00) | xoff);
            const unsigned char* a1 = x + (((e >> 10) & 0x3FFF00) | xoff);
            ldgp(buf[s][0], a0, i < n);     ldgp(buf[s][1], a0 + 128, i < n);
            ldgp(buf[s][2], a1, i + 1 < n); ldgp(buf[s][3], a1 + 128, i + 1 < n);
        }
    };

    if (warp < 8) {
        mbar_wait(SM_MBQ);
        tile_gemm(SM_WQ, SM_T, warp, lane);
    }
    __syncthreads();
    TS(9);
    const int row = warp * 4 + (g >> 1);
    const uint32_t trow = SM_T + row * 128;
    uint32_t q[4][4];
    #pragma unroll
    for (int L = 0; L < 2; L++) {
        uint4 a = lds128(trow + L * 10240 + ((t ^ (row & 7)) << 4)), b = lds128(trow + L * 10240 + (((4 + t) ^ (row & 7)) << 4));
        q[2 * L][0] = a.x; q[2 * L][1] = b.x; q[2 * L][2] = a.y; q[2 * L][3] = b.y;
        q[2 * L + 1][0] = a.z; q[2 * L + 1][1] = b.z; q[2 * L + 1][2] = a.w; q[2 * L + 1][3] = b.w;
    }
    float acc[4][4];
    #pragma unroll
    for (int i = 0; i < 4; i++) { acc[i][0] = acc[i][1] = acc[i][2] = acc[i][3] = 0.f; }

    auto compute = [&](int e0, uint4 (&v)[4]) {
        int i = e0 + 2 * t;
        uint32_t em = lds32(fl + i * 2);
        float sa[4] = {0, 0, 0, 0}, sc[4] = {0, 0, 0, 0};
        mma(sa, q[0][0], q[0][1], q[0][2], q[0][3], v[0].x, v[0].y);
        mma(sc, q[0][0], q[0][1], q[0][2], q[0][3], v[2].x, v[2].y);
        mma(sa, q[1][0], q[1][1], q[1][2], q[1][3], v[0].z, v[0].w);
        mma(sc, q[1][0], q[1][1], q[1][2], q[1][3], v[2].z, v[2].w);
        mma(sa, q[2][0], q[2][1], q[2][2], q[2][3], v[1].x, v[1].y);
        mma(sc, q[2][0], q[2][1], q[2][2], q[2][3], v[3].x, v[3].y);
        mma(sa, q[3][0], q[3][1], q[3][2], q[3][3], v[1].z, v[1].w);
        mma(sc, q[3][0], q[3][1], q[3][2], q[3][3], v[3].z, v[3].w);
        bool ma = i < n && (em & 3) == (uint32_t)(g >> 1), mb = i + 1 < n && ((em >> 16) & 3) == (uint32_t)(g >> 1);
        float aa = ma ? sigm(sa[0] + sa[3]) : 0.f, ab = mb ? sigm(sc[0] + sc[3]) : 0.f;
        uint32_t pk = pack_bf16(aa, ab);
        uint32_t b0 = (g & 1) ? (pk << 16) : (pk & 0xFFFF), b1 = (g & 1) ? (pk & 0xFFFF0000u) : (pk >> 16);
        mma(acc[0], movm(v[0].x), movm(v[0].y), movm(v[2].x), movm(v[2].y), b0, b1);
        mma(acc[1], movm(v[0].z), movm(v[0].w), movm(v[2].z), movm(v[2].w), b0, b1);
        mma(acc[2], movm(v[1].x), movm(v[1].y), movm(v[3].x), movm(v[3].y), b0, b1);
        mma(acc[3], movm(v[1].z), movm(v[1].w), movm(v[3].z), movm(v[3].w), b0, b1);
    };

    int scan = 0;
    while (true) {
        #pragma unroll 1
        for (int e0 = 0; e0 < n; e0 += 16) {
            compute(e0, buf[0]);
            if (e0 + 8 < n) compute(e0 + 8, buf[1]);
            issue(e0 + 16);
        }
        if (__builtin_expect(!slow || scan >= N_EDGES, 1)) break;
        __syncwarp();
        n = 0;
        while (scan < N_EDGES && n <= FLATCAP - 32) {
            int ee = scan + lane;
            uint32_t c = (uint32_t)(__ldg(dst + ee) - cta * TILE - warp * 4);
            uint32_t m = __ballot_sync(0xffffffffu, c < 4);
            if (c < 4) sts16(fl + (n + __popc(m & ((1u << lane) - 1))) * 2, __ldg(src + ee) * 4 + c);
            n += __popc(m);
            scan += 32;
        }
        __syncwarp();
        issue(0);
    }
    TS(10);

    #pragma unroll
    for (int L = 0; L < 2; L++) {
        uint32_t o0 = movm(pack_bf16(acc[2 * L][0], acc[2 * L][1])), o1 = movm(pack_bf16(acc[2 * L][2], acc[2 * L][3]));
        uint32_t o2 = movm(pack_bf16(acc[2 * L + 1][0], acc[2 * L + 1][1])), o3 = movm(pack_bf16(acc[2 * L + 1][2], acc[2 * L + 1][3]));
        sts128(trow + L * 10240 + (((4 * (g & 1) + t) ^ (row & 7)) << 4), o0, o1, o2, o3);
    }
    asm volatile("fence.proxy.async.shared::cta;" ::: "memory");
    if (warp < 8) mbar_wait(SM_MBV);
    __syncthreads();
    TS(11);
    if (warp < 8) tile_gemm(SM_WV, SM_T, warp, lane);
    __syncthreads();
    TS(12);
    #pragma unroll
    for (int k = 0; k < 2; k++) {
        int i = tid + k * NTHR, r = i >> 4, ch = i & 15;
        if (r < TILE && cta * TILE + r < N_NODES)
            out[cta * TILE * 16 + i] = lds128(SM_T + (ch >> 3) * 10240 + r * 128 + (((ch & 7) ^ (r & 7)) << 4));
    }
    TS(13);
    TS_DUMP();
}

typedef CUresult (*EncodeFn)(CUtensorMap*, CUtensorMapDataType, cuuint32_t, void*, const cuuint64_t*, const cuuint64_t*,
                             const cuuint32_t*, const cuuint32_t*, CUtensorMapInterleave, CUtensorMapSwizzle,
                             CUtensorMapL2promotion, CUtensorMapFloatOOBfill);

static void encode(EncodeFn fn, CUtensorMap* tm, const void* ptr, int rows, int box_rows) {
    cuuint64_t dims[2] = {128, (cuuint64_t)rows};
    cuuint64_t strides[1] = {256};
    cuuint32_t box[2] = {64, (cuuint32_t)box_rows};
    cuuint32_t es[2] = {1, 1};
    fn(tm, CU_TENSOR_MAP_DATA_TYPE_BFLOAT16, 2, (void*)ptr, dims, strides, box, es, CU_TENSOR_MAP_INTERLEAVE_NONE,
       CU_TENSOR_MAP_SWIZZLE_128B, CU_TENSOR_MAP_L2_PROMOTION_NONE, CU_TENSOR_MAP_FLOAT_OOB_FILL_NONE);
}

}

extern "C" void kernel_launch(void* const* d_in, const int* in_sizes, int n_in, void* d_out, int out_size) {
    using namespace fg;
    static int coresident = -1;
    static EncodeFn enc = nullptr;
    static Scratch* scr = nullptr;
    if (coresident < 0) {
        cudaFuncSetAttribute(fg_kernel, cudaFuncAttributeMaxDynamicSharedMemorySize, SM_ALLOC);
        int dev = 0, sms = 0, occ = 0;
        cudaGetDevice(&dev);
        cudaDeviceGetAttribute(&sms, cudaDevAttrMultiProcessorCount, dev);
        cudaOccupancyMaxActiveBlocksPerMultiprocessor(&occ, fg_kernel, NTHR, SM_ALLOC);
        coresident = (sms * occ >= NCTA) ? 1 : 0;
        cudaDriverEntryPointQueryResult qr;
        cudaGetDriverEntryPoint("cuTensorMapEncodeTiled", (void**)&enc, cudaEnableDefault, &qr);
        cudaGetSymbolAddress((void**)&scr, g_scratch);
    }
    CUtensorMap tx, tq, tv;
    encode(enc, &tx, d_in[0], N_NODES, 80);
    encode(enc, &tq, d_in[3], 128, 128);
    encode(enc, &tv, d_in[4], 128, 128);
    const unsigned char* x = (const unsigned char*)d_in[0];
    const unsigned char* wq = (const unsigned char*)d_in[3];
    const unsigned char* wv = (const unsigned char*)d_in[4];
    const int* src = (const int*)d_in[1];
    const int* dst = (const int*)d_in[2];
    if (coresident) {
        fg_kernel<<<NCTA, NTHR, SM_ALLOC, cudaStreamPerThread>>>(x, src, dst, (uint4*)d_out, scr, 3, wq, wv, tx, tq, tv);
    } else {
        fg_kernel<<<NCTA, NTHR, SM_ALLOC, cudaStreamPerThread>>>(x, src, dst, (uint4*)d_out, scr, 1, wq, wv, tx, tq, tv);
        fg_kernel<<<NCTA, NTHR, SM_ALLOC, cudaStreamPerThread>>>(x, src, dst, (uint4*)d_out, scr, 2, wq, wv, tx, tq, tv);
    }
}
```

```cpp
#include <cuda_runtime.h>
#include <cuda_bf16.h>
#include <cuda.h>
#include <stdint.h>

namespace fg {

constexpr int N_NODES = 10000;
constexpr int N_EDGES = 160000;
constexpr int NCTA    = 132;
constexpr int TILE    = 76;
constexpr int NGRP    = 19;
constexpr int NTHR    = 640;
constexpr int NPROD   = 125;
#define MP 132
constexpr int MPITCH  = MP * 4;
constexpr int SLICE   = 1280;
constexpr int BOXCAP  = 24;
constexpr int EXTCAP  = 27;
constexpr int BOXPITCH = 28;
constexpr int SUBCAP  = 64;
constexpr int FLATCAP = 128;
constexpr int POLL_LIMIT = 200;
#define DLY 450
#define DLYN 64
#define DLYM 0
#define SHARE 80
#define T_POLL 2900
#define T_X 700
#define X_STEP 450
#define T_WQ 1100
#define T_WV 13000

constexpr uint32_t SB     = 1024;
constexpr uint32_t SM_WQ   = SB;
constexpr uint32_t SM_WV   = SM_WQ + 32768;
constexpr uint32_t SM_T    = SM_WV + 32768;
constexpr uint32_t SM_SUB  = SM_T + 20480;
constexpr uint32_t SM_BOX  = SM_SUB + 128 * SUBCAP * 2;
constexpr uint32_t SM_FLAT = SM_BOX;
constexpr uint32_t FLATPITCH = (FLATCAP + 32) * 4;
constexpr uint32_t SM_CNT  = SM_BOX + NCTA * BOXPITCH * 4;
constexpr uint32_t SM_LCNT = SM_CNT + 528;
constexpr uint32_t SM_MISC = SM_LCNT + 512;
constexpr uint32_t SM_OUT  = SM_WQ;
constexpr uint32_t SM_PART = SM_WQ + 20480;
constexpr uint32_t SM_MBA  = SM_MISC + 16;
constexpr uint32_t SM_MBB  = SM_MISC + 24;
constexpr uint32_t SM_MBV  = SM_MISC + 32;
constexpr uint32_t SM_MBQ  = SM_MISC + 40;
constexpr uint32_t SM_RESC = SM_MISC + 56;
constexpr uint32_t SM_END  = SM_RESC + NCTA * 4;
constexpr int SM_TOTAL = SM_END - SB;

extern __shared__ __align__(1024) unsigned char smem[];

struct Scratch {
    uint4 mail[NCTA * MPITCH];
    uint4 ext[NCTA * NCTA];
    unsigned epoch[NCTA];
};
__device__ __align__(128) Scratch g_scratch;
#define TS(i)
#define TS_INIT()
#define TS_DUMP()
constexpr int SM_ALLOC = SM_TOTAL;

__device__ __forceinline__ uint32_t movm(uint32_t a) {
    uint32_t d; asm volatile("movmatrix.sync.aligned.m8n8.trans.b16 %0, %1;" : "=r"(d) : "r"(a)); return d;
}
__device__ __forceinline__ void mma(float (&c)[4], uint32_t a0, uint32_t a1, uint32_t a2, uint32_t a3, uint32_t b0, uint32_t b1) {
    asm volatile("mma.sync.aligned.m16n8k16.row.col.f32.bf16.bf16.f32 {%0,%1,%2,%3}, {%4,%5,%6,%7}, {%8,%9}, {%0,%1,%2,%3};"
                 : "+f"(c[0]), "+f"(c[1]), "+f"(c[2]), "+f"(c[3]) : "r"(a0), "r"(a1), "r"(a2), "r"(a3), "r"(b0), "r"(b1));
}
__device__ __forceinline__ void ldgp(uint4& v, const void* p, bool pred) {
    asm volatile("{\n.reg .pred p;\nsetp.ne.u32 p, %5, 0;\n@p ld.global.nc.v4.u32 {%0,%1,%2,%3}, [%4];\n}"
                 : "+r"(v.x), "+r"(v.y), "+r"(v.z), "+r"(v.w) : "l"(p), "r"((uint32_t)pred) : "memory");
}
__device__ __forceinline__ uint4 lds128(uint32_t a) {
    uint4 v; asm volatile("ld.shared.v4.u32 {%0,%1,%2,%3}, [%4];" : "=r"(v.x), "=r"(v.y), "=r"(v.z), "=r"(v.w) : "r"(a) : "memory"); return v;
}
__device__ __forceinline__ uint2 lds64(uint32_t a) { uint2 v; asm volatile("ld.shared.v2.u32 {%0,%1}, [%2];" : "=r"(v.x), "=r"(v.y) : "r"(a) : "memory"); return v; }
__device__ __forceinline__ uint32_t lds32(uint32_t a) { uint32_t v; asm volatile("ld.shared.u32 %0, [%1];" : "=r"(v) : "r"(a) : "memory"); return v; }
__device__ __forceinline__ uint32_t lds16(uint32_t a) { uint16_t v; asm volatile("ld.shared.u16 %0, [%1];" : "=h"(v) : "r"(a) : "memory"); return v; }
__device__ __forceinline__ void sts32(uint32_t a, uint32_t v) { asm volatile("st.shared.u32 [%0], %1;" :: "r"(a), "r"(v) : "memory"); }
__device__ __forceinline__ void sts16(uint32_t a, uint32_t v) { asm volatile("st.shared.u16 [%0], %1;" :: "r"(a), "h"((uint16_t)v) : "memory"); }
__device__ __forceinline__ uint32_t atoms_inc(uint32_t a) { uint32_t r; asm volatile("atom.shared.add.u32 %0, [%1], 1;" : "=r"(r) : "r"(a) : "memory"); return r; }
__device__ __forceinline__ void sts128(uint32_t a, uint32_t x, uint32_t y, uint32_t z, uint32_t w) {
    asm volatile("st.shared.v4.u32 [%0], {%1,%2,%3,%4};" :: "r"(a), "r"(x), "r"(y), "r"(z), "r"(w) : "memory");
}
__device__ __forceinline__ void bar_sync(int id, int n)   { asm volatile("bar.sync %0, %1;" :: "r"(id), "r"(n) : "memory"); }
__device__ __forceinline__ void bar_arrive(int id, int n) { asm volatile("bar.arrive %0, %1;" :: "r"(id), "r"(n) : "memory"); }
__device__ __forceinline__ uint32_t clock32() { uint32_t c; asm volatile("mov.u32 %0, %clock;" : "=r"(c)); return c; }
__device__ __forceinline__ void mbar_wait(uint32_t mb) {
    asm volatile("{\n.reg .pred p;\n.reg .u32 i;\nmov.u32 i, 0;\n"
                 "W: mbarrier.try_wait.parity.shared::cta.b64 p, [%0], 0;\n@p bra D;\n"
                 "add.u32 i, i, 1;\nsetp.lt.u32 p, i, 4000000;\n@p bra W;\ntrap;\nD:\n}" :: "r"(mb) : "memory");
}
__device__ __forceinline__ void tma2d(uint32_t dst, const CUtensorMap* tm, int c0, int c1, uint32_t mb) {
    asm volatile("cp.async.bulk.tensor.2d.shared::cluster.global.mbarrier::complete_tx::bytes [%0], [%1, {%2, %3}], [%4];"
                 :: "r"(dst), "l"(tm), "r"(c0), "r"(c1), "r"(mb) : "memory");
}
__device__ __forceinline__ void load_w(uint32_t dst, const CUtensorMap* tm, uint32_t mb) {
    tma2d(dst, tm, 0, 0, mb);
    tma2d(dst + 16384, tm, 64, 0, mb);
}
__device__ __forceinline__ bool mbar_test(uint32_t mb) {
    uint32_t r;
    asm volatile("{\n.reg .pred p;\nmbarrier.test_wait.parity.shared::cta.b64 p, [%1], 0;\nselp.u32 %0, 1, 0, p;\n}" : "=r"(r) : "r"(mb) : "memory");
    return r;
}
__device__ __forceinline__ uint32_t pack_bf16(float lo, float hi) {
    uint32_t r; asm("cvt.rn.bf16x2.f32 %0, %1, %2;" : "=r"(r) : "f"(hi), "f"(lo)); return r;
}
__device__ __forceinline__ float sigm(float s) {
    float e, r;
    asm("ex2.approx.ftz.f32 %0, %1;" : "=f"(e) : "f"(s * -0.12751743197f));
    asm("rcp.approx.ftz.f32 %0, %1;" : "=f"(r) : "f"(1.0f + e));
    return r;
}
__device__ __forceinline__ uint64_t make_desc(uint32_t addr) {
    return (uint64_t)((addr & 0x3FFFF) >> 4) | ((uint64_t)1 << 16) | ((uint64_t)64 << 32) | ((uint64_t)1 << 62);
}

#define WG_D8(o)  "+f"(d[o]), "+f"(d[o + 1]), "+f"(d[o + 2]), "+f"(d[o + 3]), "+f"(d[o + 4]), "+f"(d[o + 5]), "+f"(d[o + 6]), "+f"(d[o + 7])
__device__ __forceinline__ void wgmma48(float* d, uint64_t a, uint64_t b, uint32_t acc) {
    asm volatile("{\n.reg .pred p;\nsetp.ne.u32 p, %26, 0;\n"
        "wgmma.mma_async.sync.aligned.m64n48k16.f32.bf16.bf16 "
        "{%0,%1,%2,%3,%4,%5,%6,%7,%8,%9,%10,%11,%12,%13,%14,%15,%16,%17,%18,%19,%20,%21,%22,%23}, %24, %25, p, 1, 1, 1, 0;\n}"
        : WG_D8(0), WG_D8(8), WG_D8(16) : "l"(a), "l"(b), "r"(acc) : "memory");
}
__device__ __forceinline__ void wgmma32(float* d, uint64_t a, uint64_t b, uint32_t acc) {
    asm volatile("{\n.reg .pred p;\nsetp.ne.u32 p, %18, 0;\n"
        "wgmma.mma_async.sync.aligned.m64n32k16.f32.bf16.bf16 "
        "{%0,%1,%2,%3,%4,%5,%6,%7,%8,%9,%10,%11,%12,%13,%14,%15}, %16, %17, p, 1, 1, 1, 0;\n}"
        : WG_D8(0), WG_D8(8) : "l"(a), "l"(b), "r"(acc) : "memory");
}
__device__ __forceinline__ void wgmma16(float* d, uint64_t a, uint64_t b, uint32_t acc) {
    asm volatile("{\n.reg .pred p;\nsetp.ne.u32 p, %10, 0;\n"
        "wgmma.mma_async.sync.aligned.m64n16k16.f32.bf16.bf16 {%0,%1,%2,%3,%4,%5,%6,%7}, %8, %9, p, 1, 1, 1, 0;\n}"
        : WG_D8(0) : "l"(a), "l"(b), "r"(acc) : "memory");
}
__device__ __forceinline__ void stsm4t(uint32_t a, const float* d) {
    asm volatile("stmatrix.sync.aligned.m8n8.x4.trans.shared.b16 [%0], {%1,%2,%3,%4};"
                 :: "r"(a), "r"(pack_bf16(d[0], d[1])), "r"(pack_bf16(d[2], d[3])), "r"(pack_bf16(d[4], d[5])), "r"(pack_bf16(d[6], d[7])) : "memory");
}

__device__ __forceinline__ uint32_t make_entry(uint32_t s, uint32_t dl) { return s * 4 + dl + (dl >> 2) * 65532u; }
__device__ __forceinline__ void st_b128(void* p, uint32_t a, uint32_t b, uint32_t c, uint32_t d) {
    asm volatile("{\n.reg .b128 v;\n.reg .b64 lo, hi;\nmov.b64 lo, {%1,%2};\nmov.b64 hi, {%3,%4};\nmov.b128 v, {lo, hi};\n"
                 "st.relaxed.gpu.global.b128 [%0], v;\n}" :: "l"(p), "r"(a), "r"(b), "r"(c), "r"(d) : "memory");
}
__device__ __forceinline__ uint4 ld_b128(const void* p) {
    uint4 w;
    asm volatile("{\n.reg .b128 v;\n.reg .b64 lo, hi;\nld.relaxed.gpu.global.b128 v, [%4];\nmov.b128 {lo, hi}, v;\n"
                 "mov.b64 {%0,%1}, lo;\nmov.b64 {%2,%3}, hi;\n}" : "=r"(w.x), "=r"(w.y), "=r"(w.z), "=r"(w.w) : "l"(p) : "memory");
    return w;
}
__device__ __forceinline__ uint4 ldg128(const void* p) {
    uint4 v; asm volatile("ld.global.nc.v4.u32 {%0,%1,%2,%3}, [%4];" : "=r"(v.x), "=r"(v.y), "=r"(v.z), "=r"(v.w) : "l"(p) : "memory"); return v;
}
template <int K>
__device__ __forceinline__ void insert(const uint32_t (&e)[K]) {
    uint32_t pos[K];
    #pragma unroll
    for (int k = 0; k < K; k++) asm volatile("atom.shared.add.u32 %0, [%1], 2;" : "=r"(pos[k]) : "r"(SM_LCNT + ((e[k] >> 12) & 0x1FC)) : "memory");
    #pragma unroll
    for (int k = 0; k < K; k++) sts16(SM_SUB + (((e[k] >> 7) & 0x3F80) | (pos[k] & (2 * SUBCAP - 2))), e[k]);
}

__device__ __forceinline__ void bin(int2 d2, int2 s2) {
    uint32_t tl0 = __umulhi(d2.x, 56512728u), tl1 = __umulhi(d2.y, 56512728u);
    uint32_t p0 = atoms_inc(SM_CNT + tl0 * 4), p1 = atoms_inc(SM_CNT + tl1 * 4);
    sts32(SM_BOX + tl0 * (BOXPITCH * 4) + min(p0, (uint32_t)EXTCAP) * 4, make_entry(s2.x, d2.x - tl0 * TILE));
    sts32(SM_BOX + tl1 * (BOXPITCH * 4) + min(p1, (uint32_t)EXTCAP) * 4, make_entry(s2.y, d2.y - tl1 * TILE));
}
template <int N>
__device__ __forceinline__ void q_gemm(int r0, int warp, int lane) {
    float d[N];
    const uint64_t da = make_desc(SM_WQ), db = make_desc(SM_T + r0 * 128);
    asm volatile("wgmma.fence.sync.aligned;" ::: "memory");
    #pragma unroll
    for (int s = 0; s < 16; s++) {
        const int h = s & 1, k = s >> 1;
        const uint64_t a = da + (uint64_t)(h * 1024 + k * 128), b = db + (uint64_t)((k >> 2) * 640 + (k & 3) * 2);
        if (N == 48) wgmma48(d + h * (N / 2), a, b, k != 0); else wgmma32(d + h * (N / 2), a, b, k != 0);
    }
    asm volatile("wgmma.commit_group.sync.aligned;" ::: "memory");
    asm volatile("wgmma.wait_group.sync.aligned 0;" ::: "memory");
    bar_sync(1, 128);
    const int r = lane & 7;
    const uint32_t base = SM_T + (r0 + (lane >> 4) * 8 + r) * 128 + (((2 * (warp & 3) + ((lane >> 3) & 1)) ^ r) << 4);
    #pragma unroll
    for (int i = 0; i < N / 8; i++) stsm4t(base + (i / (N / 16)) * 10240 + (i % (N / 16)) * 2048, d + i * 8);
}

__global__ void __launch_bounds__(NTHR, 1)
fg_kernel(const unsigned char* __restrict__ x, const int* __restrict__ src, const int* __restrict__ dst,
          uint4* __restrict__ out, Scratch* __restrict__ scr, int mode,
          const unsigned char* __restrict__ wq, const unsigned char* __restrict__ wv,
          const __grid_constant__ CUtensorMap tm_x, const __grid_constant__ CUtensorMap tm_wq, const __grid_constant__ CUtensorMap tm_wv) {
    const int tid = threadIdx.x, cta = blockIdx.x;
    const int e2 = cta * (SLICE / 2) + tid;
    const bool has_e = tid < NGRP * 32 && cta < NPROD;
    int2 d2, s2;
    asm volatile("{\n.reg .pred p;\nsetp.ne.u32 p, %6, 0;\n@p ld.global.nc.v2.u32 {%0,%1}, [%4];\n@p ld.global.nc.v2.u32 {%2,%3}, [%5];\n}"
                 : "=r"(d2.x), "=r"(d2.y), "=r"(s2.x), "=r"(s2.y) : "l"((const int2*)dst + e2), "l"((const int2*)src + e2), "r"((uint32_t)has_e) : "memory");
    const uint32_t t_start = clock32();
    const int warp = tid >> 5, lane = tid & 31;
    const int g = lane >> 2, t = lane & 3;
    TS_INIT();
    TS(0);
    uint32_t q[4][4];
    bool have_q = false;
    auto load_q = [&](int grp) {
        const int row = grp * 4 + (g >> 1);
        const uint32_t trow = SM_T + row * 128;
        #pragma unroll
        for (int L = 0; L < 2; L++) {
            uint4 a = lds128(trow + L * 10240 + ((t ^ (row & 7)) << 4)), b = lds128(trow + L * 10240 + (((4 + t) ^ (row & 7)) << 4));
            q[2 * L][0] = a.x; q[2 * L][1] = b.x; q[2 * L][2] = a.y; q[2 * L][3] = b.y;
            q[2 * L + 1][0] = a.z; q[2 * L + 1][1] = b.z; q[2 * L + 1][2] = a.w; q[2 * L + 1][3] = b.w;
        }
    };
    if (warp == NGRP) {
        if (lane == 0 && (mode & 2)) {
            if (cta < 128) {
                asm volatile("cp.async.bulk.prefetch.L2.global [%0], 256;" :: "l"(wq + cta * 256) : "memory");
                asm volatile("cp.async.bulk.prefetch.L2.global [%0], 256;" :: "l"(wv + cta * 256) : "memory");
            }
            if ((uint32_t)__cvta_generic_to_shared(smem) != SB) __trap();
            asm volatile("prefetch.tensormap [%0];" :: "l"(&tm_x) : "memory");
            asm volatile("prefetch.tensormap [%0];" :: "l"(&tm_wq) : "memory");
            asm volatile("prefetch.tensormap [%0];" :: "l"(&tm_wv) : "memory");
            asm volatile("mbarrier.init.shared::cta.b64 [%0], 1;" :: "r"(SM_MBA) : "memory");
            asm volatile("mbarrier.init.shared::cta.b64 [%0], 1;" :: "r"(SM_MBB) : "memory");
            asm volatile("mbarrier.init.shared::cta.b64 [%0], 1;" :: "r"(SM_MBV) : "memory");
            asm volatile("mbarrier.init.shared::cta.b64 [%0], 128;" :: "r"(SM_MBQ) : "memory");
            asm volatile("mbarrier.init.shared::cta.b64 [%0], 128;" :: "r"(SM_MBQ + 8) : "memory");
            asm volatile("fence.proxy.async.shared::cta;" ::: "memory");
            asm volatile("mbarrier.arrive.expect_tx.shared::cta.b64 _, [%0], %1;" :: "r"(SM_MBA), "r"(32768 + 48 * 256) : "memory");
            asm volatile("mbarrier.arrive.expect_tx.shared::cta.b64 _, [%0], %1;" :: "r"(SM_MBB), "r"(32 * 256) : "memory");
            asm volatile("mbarrier.arrive.expect_tx.shared::cta.b64 _, [%0], %1;" :: "r"(SM_MBV), "r"(32768) : "memory");
        }
        __syncwarp();
        bar_arrive(3, NTHR);
        if (!(mode & 2)) return;
        #pragma unroll
        for (int k = 0; k <= 5; k++) {
            const int tk = k < 5 ? T_X + k * X_STEP : 1 << 30, tp = k ? T_X + (k - 1) * X_STEP : -1;
            if (T_WQ < tk && T_WQ >= tp) {
                while (clock32() - t_start < T_WQ) {}
                if (lane == 0) load_w(SM_WQ, &tm_wq, SM_MBA);
            }
            if (k < 5) {
                while (clock32() - t_start < tk) {}
                if (lane == 0) {
                    tma2d(SM_T + k * 2048, &tm_x, 0, cta * TILE + k * 16, k < 3 ? SM_MBA : SM_MBB);
                    tma2d(SM_T + 10240 + k * 2048, &tm_x, 64, cta * TILE + k * 16, k < 3 ? SM_MBA : SM_MBB);
                }
            }
        }
        while (clock32() - t_start < T_POLL) {}
        __syncwarp();
        bar_arrive(11, 544);
    } else {
        int2 d3 = make_int2(-1, 0), s3 = make_int2(0, 0);
        if (warp == 18 && cta < NPROD) { d3 = __ldg((const int2*)dst + e2 + 32); s3 = __ldg((const int2*)src + e2 + 32); }
        unsigned epoch = 0;
        if (tid == 0) epoch = __ldcg(&scr->epoch[cta]);
        const bool act = tid < NCTA * 4 && cta < NPROD && (mode & 1);
        uint4* wp = scr->mail + (tid >> 2) * MPITCH + cta * 4 + t;
        if (tid < 132 + 128 + 1) sts32(SM_CNT + tid * 4, 0);
        {
            const uint32_t dm = (96 + ((4 * cta) & 31)) << 14;
            sts128(SM_BOX + tid * 16, dm, dm + (1 << 14), dm + (2 << 14), dm + (3 << 14));
            if (tid < NCTA * 7 - NGRP * 32) sts128(SM_BOX + (tid + NGRP * 32) * 16, dm, dm + (1 << 14), dm + (2 << 14), dm + (3 << 14));
        }
        bar_sync(2, NGRP * 32);
        TS(1);

        if (has_e) bin(d2, s2);
        if (warp == 18 && d3.x >= 0) bin(d3, s3);
        if (tid == 0) {
            sts32(SM_MISC + 8, epoch + 1);
            if (mode & 2) scr->epoch[cta] = epoch + 1;
        }
        bar_sync(3, NTHR);
        TS(2);
        const uint32_t tag = lds32(SM_MISC + 8), par = tag << 31;
        if (act) {
            const uint32_t bp = SM_BOX + (tid >> 2) * (BOXPITCH * 4) + t * 4;
            uint32_t c = lds32(SM_CNT + (tid >> 2) * 4);
            uint32_t e[6];
            #pragma unroll
            for (int k = 0; k < 6; k++) e[k] = lds32(bp + k * 16);
            if (__builtin_expect(c > BOXCAP, 0)) {
                if (c > EXTCAP) {
                    #pragma unroll
                    for (int k = 0; k < 6; k++) e[k] = (80 + (lane & 15)) << 14;
                } else if (t == 3) {
                    const uint32_t a = lds32(bp + 21 * 4), b = lds32(bp + 22 * 4);
                    st_b128(scr->ext + (tid >> 2) * NCTA + cta, e[5] | (a << 21), (a >> 11) | (b << 10), lds32(bp + 23 * 4), tag);
                    e[5] = 80 << 14;
                }
            }
            st_b128(wp, e[0] | (e[1] << 21), (e[1] >> 11) | (e[2] << 10) | 0x80000000u,
                        e[3] | (e[4] << 21), (e[4] >> 11) | (e[5] << 10) | par);
        }
        if (!(mode & 2)) return;
        TS(3);

        if (warp < 16) {
            const uint4* mp = scr->mail + cta * MPITCH + tid;
            const uint32_t dm = (96 + lane) << 14;
            const uint4 wd = make_uint4(dm | (dm << 21), (dm >> 11) | (dm << 10), dm | (dm << 21), (dm >> 11) | (dm << 10));
            uint4 w = wd;
            bool ok = tid >= NPROD * 4;
            int it = 0;
            bar_sync(11, 544);
            do {
                if (!ok) { w = ld_b128(mp); ok = (int)(w.y & ~(w.w ^ par)) < 0; }
            } while (__builtin_expect(!__all_sync(0xffffffffu, ok), 0) && ++it < POLL_LIMIT);
            TS(4);
            const bool bad = !ok || (w.x & (0x70 << 14)) == (0x50 << 14);
            if (__builtin_expect(__any_sync(0xffffffffu, bad), 0)) {
                if ((__ballot_sync(0xffffffffu, bad) >> (lane & ~3)) & 0xF) {
                    w = wd;
                    if (t == 0) sts32(SM_RESC + atoms_inc(SM_MISC) * 4, tid >> 2);
                }
            }
            const uint32_t e1 = __funnelshift_r(w.x, w.y, 21), e4 = __funnelshift_r(w.z, w.w, 21);
            insert<4>({w.x, e1, w.y >> 10, w.z});
            if (__builtin_expect(__any_sync(0xffffffffu, (e4 & (0x60 << 14)) != (0x60 << 14)), 0)) {
                insert<2>({e4, w.w >> 10});
                if (((w.w >> 10) & (0x70 << 14)) == (0x50 << 14)) {
                    it = 0;
                    do { w = ld_b128(scr->ext + cta * NCTA + (tid >> 2)); } while (w.w != tag && ++it < POLL_LIMIT);
                    if (w.w == tag) insert<4>({w.x, __funnelshift_r(w.x, w.y, 21), w.y >> 10, w.z});
                    else for (int k = 0; k < NGRP; k++) atomicAdd((unsigned*)(smem + SM_LCNT - SB) + 4 * k + 2, 1u << 20);
                }
                __syncwarp();
            }
            if (warp < 12 && mbar_test(SM_MBQ)) { load_q(warp); have_q = true; }
            bar_arrive(4, NTHR);
            bar_sync(2, 512);
        }
    }
    if (warp >= 16) {
        mbar_wait(SM_MBA);
        TS(12);
        q_gemm<48>(0, warp, lane);
        asm volatile("mbarrier.arrive.shared::cta.b64 _, [%0];" :: "r"(SM_MBQ) : "memory");
        TS(6);
        mbar_wait(SM_MBB);
        TS(15);
        bar_sync(4, NTHR);
        q_gemm<32>(48, warp, lane);
        asm volatile("mbarrier.arrive.shared::cta.b64 _, [%0];" :: "r"(SM_MBQ + 8) : "memory");
        TS(8);
    }
    TS(5);

    const int wg = warp >> 2;
    {
        uint4 buf[2][4];
        const uint32_t fl = SM_FLAT + warp * FLATPITCH;
        const uint32_t xoff = (4 * (g & 1) + t) * 16;
        auto widen = [&](uint32_t u) { return ((u << 6) & 0x3FFF00) | (u & 3); };
        const uint32_t sp = SM_SUB + warp * (4 * SUBCAP * 2);
        uint32_t f0, f1, raw[3];
        uint4 c, cw;
        for (bool again = false;; again = true) {
            f0 = lds32(sp + (g >> 1) * 4); f1 = lds32(sp + 16 + (g >> 1) * 4);
            c = lds128(SM_LCNT + warp * 16);
            const int nres = lds32(SM_MISC);
            #pragma unroll
            for (int b = 0; b < 3; b++) raw[b] = lds32(sp + b * (SUBCAP * 2) + lane * 4);
            cw = lds128(SM_LCNT + min(lane, NGRP) * 16);
            if (__builtin_expect(nres == 0 || again, 1)) break;
            bar_sync(5, NTHR);
            #pragma unroll 1
            for (int k = 0; k < nres; k++) {
                const int e0 = lds32(SM_RESC + k * 4) * SLICE;
                #pragma unroll 1
                for (int i = tid; i < SLICE; i += NTHR) {
                    uint32_t dl = (uint32_t)(__ldg(dst + e0 + i) - cta * TILE);
                    if (dl < TILE) insert<1>({make_entry(__ldg(src + e0 + i), dl)});
                }
            }
            bar_sync(5, NTHR);
        }
        int n = (c.x + c.y + c.z) >> 1;
        uint32_t nw = max(max(cw.x, cw.y), cw.z) > 2 * SUBCAP ? 4096 : (cw.x + cw.y + cw.z) >> 1;
        const bool direct = c.x >= 32 && c.x <= 2 * SUBCAP;
        if (DLY && n <= DLYN) { const uint32_t t1 = clock32(); while (clock32() - t1 < DLY) {} }
        #pragma unroll
        for (int s = 0; s < 2; s++) {
            const uint32_t e = direct ? (s ? f1 : f0) : nw >> 30;
            const unsigned char* a0 = x + (((e << 6) & 0x3FFF00) | xoff);
            const unsigned char* a1 = x + (((e >> 10) & 0x3FFF00) | xoff);
            buf[s][0] = ldg128(a0); buf[s][1] = ldg128(a0 + 128);
            buf[s][2] = ldg128(a1); buf[s][3] = ldg128(a1 + 128);
        }
        TS(7);
        auto issue8 = [&](uint32_t pe, uint4 (&b)[4]) {
            const uint2 e = lds64(pe);
            const unsigned char* a0 = x + ((e.x & 0xFFFFFF00u) | xoff);
            const unsigned char* a1 = x + ((e.y & 0xFFFFFF00u) | xoff);
            ldgp(b[0], a0, !(e.x & 4)); ldgp(b[1], a0 + 128, !(e.x & 4));
            ldgp(b[2], a1, !(e.y & 4)); ldgp(b[3], a1 + 128, !(e.y & 4));
        };
        uint32_t longs = __ballot_sync(0xffffffffu, nw > SHARE && nw <= FLATCAP);
        const uint32_t shorts = __ballot_sync(0xffffffffu, nw <= SHARE - 16 && lane <= NGRP);
        const int npair = min(min(__popc(longs), __popc(shorts)), 4);
        const int kl = __popc(longs & ((1u << warp) - 1)), ks = __popc(shorts >> warp >> 1);
        const bool helped = ((longs >> warp) & 1) && kl < npair, helps = ((shorts >> warp) & 1) && ks < npair;
        uint32_t st = helped ? 3 | (kl << 3) : 0;
        if (__builtin_expect(max(max(c.x, c.y), c.z) > 2 * SUBCAP || n > FLATCAP, 0)) { st = 4; n = 0; }
        if (helped) n = SHARE;
        #pragma unroll
        for (int b = 0; b < 3; b++) {
            const uint32_t cb = b == 0 ? c.x : b == 1 ? c.y : c.z, p = ((b == 0 ? 0 : b == 1 ? c.x : c.x + c.y) >> 1) + 2 * lane;
            if (4 * lane < cb && p < n) sts32(fl + p * 4, widen(raw[b]));
            if (4 * lane + 2 < cb && p + 1 < n) sts32(fl + p * 4 + 4, widen(raw[b] >> 16));
        }
        sts32(fl + (n + lane) * 4, 4);
        if (__builtin_expect(helps, 0)) {
            #pragma unroll 1
            for (int k = 0; k < ks; k++) longs &= longs - 1;
            const int victim = __ffs(longs) - 1;
            const uint4 cv = lds128(SM_LCNT + victim * 16);
            const int extra = ((cv.x + cv.y + cv.z) >> 1) - SHARE;
            st = 1 | (ks << 3) | (victim << 5) | (extra << 10);
            __syncwarp();
            #pragma unroll
            for (int k = 0; k < 3; k++) {
                const uint32_t f = 2 * (SHARE + lane + 32 * k);
                const uint32_t u = lds16(SM_SUB + victim * (4 * SUBCAP * 2) + ((f + (f >= cv.x ? 2 * SUBCAP - cv.x : 0) + (f >= cv.x + cv.y ? 2 * SUBCAP - cv.y : 0)) & (8 * SUBCAP - 2)));
                if (((n + 15) & ~15) + lane + 32 * k < FLATCAP + 32) sts32(fl + (((n + 15) & ~15) + lane + 32 * k) * 4, lane + 32 * k < extra ? widen(u) : 4);
            }
        }
        __syncwarp();
        uint32_t pa = fl + 8 * t, pb = fl + 8 * (g >> 1), pend = pa + 4 * n;
        if (__builtin_expect(!direct, 0)) { issue8(pb, buf[0]); issue8(pb + 32, buf[1]); }
        if (!have_q) { mbar_wait(SM_MBQ + (warp < 12 ? 0 : 8)); load_q(warp); }
        TS(9);
        float acc[4][4];
        #pragma unroll
        for (int i = 0; i < 4; i++) { acc[i][0] = acc[i][1] = acc[i][2] = acc[i][3] = 0.f; }

        auto logits = [&](uint4 (&v)[4], float (&sa)[4], float (&sc)[4], int k) {
            const uint4 &a = v[k >> 1], &b = v[2 + (k >> 1)];
            mma(sa, q[k][0], q[k][1], q[k][2], q[k][3], (k & 1) ? a.z : a.x, (k & 1) ? a.w : a.y);
            mma(sc, q[k][0], q[k][1], q[k][2], q[k][3], (k & 1) ? b.z : b.x, (k & 1) ? b.w : b.y);
        };
        auto weights = [&](uint2 em, const float (&sa)[4], const float (&sc)[4]) {
            float aa = sigm(sa[0] + sa[3]), ab = sigm(sc[0] + sc[3]);
            return pack_bf16(((em.x ^ (g >> 1)) & 7) ? 0.f : aa, ((em.y ^ (g >> 1)) & 7) ? 0.f : ab);
        };
        auto accumulate = [&](uint4 (&v)[4], uint32_t pk) {
            uint32_t b0 = (g & 1) ? (pk << 16) : (pk & 0xFFFF), b1 = (g & 1) ? (pk & 0xFFFF0000u) : (pk >> 16);
            mma(acc[0], movm(v[0].x), movm(v[0].y), movm(v[2].x), movm(v[2].y), b0, b1);
            mma(acc[1], movm(v[0].z), movm(v[0].w), movm(v[2].z), movm(v[2].w), b0, b1);
            mma(acc[2], movm(v[1].x), movm(v[1].y), movm(v[3].x), movm(v[3].y), b0, b1);
            mma(acc[3], movm(v[1].z), movm(v[1].w), movm(v[3].z), movm(v[3].w), b0, b1);
        };
        auto flush = [&]() {
            const int row = warp * 4 + (g >> 1);
            #pragma unroll
            for (int L = 0; L < 2; L++) {
                uint32_t o0 = movm(pack_bf16(acc[2 * L][0], acc[2 * L][1])), o1 = movm(pack_bf16(acc[2 * L][2], acc[2 * L][3]));
                uint32_t o2 = movm(pack_bf16(acc[2 * L + 1][0], acc[2 * L + 1][1])), o3 = movm(pack_bf16(acc[2 * L + 1][2], acc[2 * L + 1][3]));
                sts128(SM_T + row * 128 + L * 10240 + (((4 * (g & 1) + t) ^ (row & 7)) << 4), o0, o1, o2, o3);
            }
            asm volatile("fence.proxy.async.shared::cta;" ::: "memory");
        };

        while (true) {
            #pragma unroll 1
            for (; pa < pend; pa += 64, pb += 64) {
                const uint2 em0 = lds64(pa), em1 = lds64(pa + 32);
                float s0[4] = {0, 0, 0, 0}, s1[4] = {0, 0, 0, 0}, s2[4] = {0, 0, 0, 0}, s3[4] = {0, 0, 0, 0};
                #pragma unroll
                for (int k = 0; k < 4; k++) { logits(buf[0], s0, s1, k); logits(buf[1], s2, s3, k); }
                const uint32_t p0 = weights(em0, s0, s1), p1 = weights(em1, s2, s3);
                accumulate(buf[0], p0);
                issue8(pb + 64, buf[0]);
                accumulate(buf[1], p1);
                issue8(pb + 96, buf[1]);
            }
            asm volatile("" : "+r"(st));
            if (__builtin_expect((st & 7) == 1, 0)) {
                flush();
                load_q((st >> 5) & 31);
                #pragma unroll
                for (int i = 0; i < 4; i++) { acc[i][0] = acc[i][1] = acc[i][2] = acc[i][3] = 0.f; }
                pend = pa + 4 * (st >> 10);
                st++;
                continue;
            }
            if (__builtin_expect(!(st & 4) || (st >> 3) >= N_EDGES, 1)) break;
            __syncwarp();
            int m = 0, scan = st >> 3;
            while (scan < N_EDGES && m <= FLATCAP - 32) {
                int ee = scan + lane;
                uint32_t cc = (uint32_t)(__ldg(dst + ee) - cta * TILE - warp * 4);
                uint32_t bm = __ballot_sync(0xffffffffu, cc < 4);
                if (cc < 4) sts32(fl + (m + __popc(bm & ((1u << lane) - 1))) * 4, __ldg(src + ee) * 256 + cc);
                m += __popc(bm);
                scan += 32;
            }
            st = 4 | (scan << 3);
            sts32(fl + (m + lane) * 4, 4);
            __syncwarp();
            pa = fl + 8 * t; pb = fl + 8 * (g >> 1); pend = pa + 4 * m;
            issue8(pb, buf[0]);
            issue8(pb + 32, buf[1]);
        }
        TS(10);
        const uint32_t pp = SM_PART + (st & 24) * 256 + lane * 16;
        if (__builtin_expect((st & 7) == 2, 0)) {
            mbar_wait(SM_MBQ + 8);
            #pragma unroll
            for (int i = 0; i < 4; i++)
                sts128(pp + i * 512, __float_as_uint(acc[i][0]), __float_as_uint(acc[i][1]), __float_as_uint(acc[i][2]), __float_as_uint(acc[i][3]));
            bar_arrive(12 + ((st >> 3) & 3), 64);
        } else {
            if (__builtin_expect((st & 7) == 3, 0)) {
                bar_sync(12 + ((st >> 3) & 3), 64);
                #pragma unroll
                for (int i = 0; i < 4; i++) {
                    const uint4 p = lds128(pp + i * 512);
                    acc[i][0] += __uint_as_float(p.x); acc[i][1] += __uint_as_float(p.y); acc[i][2] += __uint_as_float(p.z); acc[i][3] += __uint_as_float(p.w);
                }
            }
            flush();
        }
        if (warp == NGRP) {
            while (clock32() - t_start < T_WV) __nanosleep(100);
            if (lane == 0) load_w(SM_WV, &tm_wv, SM_MBV);
            __syncwarp();
        }
    }

    {
        mbar_wait(SM_MBV);
        bar_sync(6 + wg, 128);
        TS(11);
        float d[32];
        const uint64_t da = make_desc(SM_WV), db = make_desc(SM_T + wg * 2048);
        asm volatile("wgmma.fence.sync.aligned;" ::: "memory");
        #pragma unroll
        for (int s = 0; s < 16; s++) {
            const int h = s & 1, kh = (s >> 1) & 1, k = s >> 2;
            wgmma16(d + (kh * 2 + h) * 8, da + (uint64_t)(h * 1024 + (kh * 4 + k) * 128), db + (uint64_t)(kh * 640 + k * 2), k != 0);
        }
        asm volatile("wgmma.commit_group.sync.aligned;" ::: "memory");
        asm volatile("wgmma.wait_group.sync.aligned 0;" ::: "memory");
        #pragma unroll
        for (int i = 0; i < 16; i++) d[i] += d[16 + i];
        const uint32_t so = SM_OUT + wg * 4096;
        const int r = lane & 7;
        const uint32_t base = so + ((lane >> 4) * 8 + r) * 256 + (((2 * (warp & 3) + ((lane >> 3) & 1)) ^ r) << 4);
        stsm4t(base, d);
        stsm4t(base + 128, d + 8);
        bar_sync(6 + wg, 128);
        #pragma unroll
        for (int k = 0; k < 2; k++) {
            const int i = (tid & 127) + k * 128, rr = i >> 4, ch = i & 15, nl = wg * 16 + rr;
            if (nl < TILE && cta * TILE + nl < N_NODES)
                out[(cta * TILE + wg * 16) * 16 + i] = lds128(so + rr * 256 + ((ch ^ (rr & 7)) << 4));
        }
    }
    TS(13);
    TS_DUMP();
}

typedef CUresult (*EncodeFn)(CUtensorMap*, CUtensorMapDataType, cuuint32_t, void*, const cuuint64_t*, const cuuint64_t*,
                             const cuuint32_t*, const cuuint32_t*, CUtensorMapInterleave, CUtensorMapSwizzle,
                             CUtensorMapL2promotion, CUtensorMapFloatOOBfill);

static void encode(EncodeFn fn, CUtensorMap* tm, const void* ptr, int rows, int box_rows) {
    cuuint64_t dims[2] = {128, (cuuint64_t)rows};
    cuuint64_t strides[1] = {256};
    cuuint32_t box[2] = {64, (cuuint32_t)box_rows};
    cuuint32_t es[2] = {1, 1};
    fn(tm, CU_TENSOR_MAP_DATA_TYPE_BFLOAT16, 2, (void*)ptr, dims, strides, box, es, CU_TENSOR_MAP_INTERLEAVE_NONE,
       CU_TENSOR_MAP_SWIZZLE_128B, CU_TENSOR_MAP_L2_PROMOTION_NONE, CU_TENSOR_MAP_FLOAT_OOB_FILL_NONE);
}

}

extern "C" void kernel_launch(void* const* d_in, const int* in_sizes, int n_in, void* d_out, int out_size) {
    using namespace fg;
    static int coresident = -1;
    static EncodeFn enc = nullptr;
    static Scratch* scr = nullptr;
    if (coresident < 0) {
        cudaFuncSetAttribute(fg_kernel, cudaFuncAttributeMaxDynamicSharedMemorySize, SM_ALLOC);
        int dev = 0, sms = 0, occ = 0;
        cudaGetDevice(&dev);
        cudaDeviceGetAttribute(&sms, cudaDevAttrMultiProcessorCount, dev);
        cudaOccupancyMaxActiveBlocksPerMultiprocessor(&occ, fg_kernel, NTHR, SM_ALLOC);
        coresident = (sms * occ >= NCTA) ? 1 : 0;
        cudaDriverEntryPointQueryResult qr;
        cudaGetDriverEntryPoint("cuTensorMapEncodeTiled", (void**)&enc, cudaEnableDefault, &qr);
        cudaGetSymbolAddress((void**)&scr, g_scratch);
    }
    CUtensorMap tx, tq, tv;
    encode(enc, &tx, d_in[0], N_NODES, 16);
    encode(enc, &tq, d_in[3], 128, 128);
    encode(enc, &tv, d_in[4], 128, 128);
    const unsigned char* x = (const unsigned char*)d_in[0];
    const unsigned char* wq = (const unsigned char*)d_in[3];
    const unsigned char* wv = (const unsigned char*)d_in[4];
    const int* src = (const int*)d_in[1];
    const int* dst = (const int*)d_in[2];
    if (coresident) {
        fg_kernel<<<NCTA, NTHR, SM_ALLOC, cudaStreamPerThread>>>(x, src, dst, (uint4*)d_out, scr, 3, wq, wv, tx, tq, tv);
    } else {
        fg_kernel<<<NCTA, NTHR, SM_ALLOC, cudaStreamPerThread>>>(x, src, dst, (uint4*)d_out, scr, 1, wq, wv, tx, tq, tv);
        fg_kernel<<<NCTA, NTHR, SM_ALLOC, cudaStreamPerThread>>>(x, src, dst, (uint4*)d_out, scr, 2, wq, wv, tx, tq, tv);
    }
}
```

```cpp
#include <cuda_runtime.h>
#include <cuda_bf16.h>
#include <cuda.h>
#include <stdint.h>

namespace fg {

constexpr int N_NODES = 10000;
constexpr int N_EDGES = 160000;
constexpr int NCTA    = 132;
constexpr int TILE    = 76;
constexpr int NGRP    = 19;
constexpr int NTHR    = 640;
constexpr int NPROD   = 128;
constexpr int MP = 132;
constexpr int MPITCH  = MP * 4;
constexpr int SLICE   = 1250;
constexpr int BOXCAP  = 24;
constexpr int EXTCAP  = 30;
constexpr int BOXPITCH = 36;
constexpr int FCAP    = 128;
constexpr int PCAP    = 57;
constexpr int HWN = 12;
constexpr int HW      = HWN;
constexpr int POLL_LIMIT = 200;
constexpr int T_POLL = 3300;
constexpr int T_X = 700;
constexpr int X_STEP = 450;
constexpr int T_WQ = 1000;
constexpr int T_WV = 1950;


constexpr uint32_t SB     = 1024;
constexpr uint32_t SM_WQ   = SB;
constexpr uint32_t SM_O    = SM_WQ;
constexpr uint32_t SM_WV   = SM_WQ + 32768;
constexpr uint32_t SM_T    = SM_WV + 32768;
constexpr uint32_t SM_SUB  = SM_T + 20480;
constexpr uint32_t SM_FOR  = SM_SUB + TILE * 256;
constexpr uint32_t SM_BOX  = SM_FOR + FCAP * 16;
constexpr uint32_t SM_PART = SM_BOX;
constexpr uint32_t SM_CNT  = SM_BOX + NCTA * BOXPITCH * 4;
constexpr uint32_t SM_LCNT = SM_CNT + 528;
constexpr uint32_t SM_MISC = SM_LCNT + TILE * 32;
constexpr uint32_t SM_MBA  = SM_MISC + 24;
constexpr uint32_t SM_MBB  = SM_MISC + 32;
constexpr uint32_t SM_MBV  = SM_MISC + 40;
constexpr uint32_t SM_MBQ  = SM_MISC + 48;
constexpr uint32_t SM_MBF  = SM_MISC + 64;
constexpr uint32_t SM_MBL  = SM_MISC + 72;
constexpr uint32_t SM_MBP  = SM_MISC + 80;
constexpr uint32_t SM_RESC = SM_MBP + PCAP * 8;
constexpr uint32_t SM_END  = SM_RESC + NCTA * 4;
constexpr int SM_TOTAL = SM_END - SB;
static_assert(PCAP * 256 <= NCTA * BOXPITCH * 4 && SM_MISC % 16 == 0, "");

extern __shared__ __align__(1024) unsigned char smem[];

struct Scratch {
    uint4 mail[NCTA * MPITCH];
    uint4 ext[NCTA * NCTA * 2];
    unsigned epoch[NCTA];
};
__device__ float4 g_facc[NCTA * NTHR * 4];
__device__ __align__(128) Scratch g_scratch;
constexpr int SM_ALLOC = SM_TOTAL;

__device__ __forceinline__ void mma(float (&c)[4], uint32_t a0, uint32_t a1, uint32_t a2, uint32_t a3, uint32_t b0, uint32_t b1) {
    asm volatile("mma.sync.aligned.m16n8k16.row.col.f32.bf16.bf16.f32 {%0,%1,%2,%3}, {%4,%5,%6,%7}, {%8,%9}, {%0,%1,%2,%3};"
                 : "+f"(c[0]), "+f"(c[1]), "+f"(c[2]), "+f"(c[3]) : "r"(a0), "r"(a1), "r"(a2), "r"(a3), "r"(b0), "r"(b1));
}
template <int HI>
__device__ __forceinline__ void ldrow(uint4& u, uint4& v, uint32_t w, uint64_t base) {
    asm volatile("{\n.reg .pred p;\n.reg .b32 t;\n.reg .b64 a;\n"
                 "lop3.b32 t, %8, %10, 0, 0x0c;\nsetp.ne.u32 p, t, 0;\n"
                 "prmt.b32 t, %8, 0, %11;\nmad.wide.u32 a, t, 256, %9;\n"
                 "@p ld.global.nc.v4.u32 {%0,%1,%2,%3}, [a];\n@p ld.global.nc.v4.u32 {%4,%5,%6,%7}, [a+128];\n}"
                 : "+r"(u.x), "+r"(u.y), "+r"(u.z), "+r"(u.w), "+r"(v.x), "+r"(v.y), "+r"(v.z), "+r"(v.w)
                 : "r"(w), "l"(base), "n"(HI ? 0x30000000u : 0x3000u), "n"(HI ? 0x4432 : 0x4410) : "memory");
}
__device__ __forceinline__ uint4 lds128(uint32_t a) {
    uint4 v; asm volatile("ld.shared.v4.u32 {%0,%1,%2,%3}, [%4];" : "=r"(v.x), "=r"(v.y), "=r"(v.z), "=r"(v.w) : "r"(a) : "memory"); return v;
}
__device__ __forceinline__ uint2 lds64(uint32_t a) { uint2 v; asm volatile("ld.shared.v2.u32 {%0,%1}, [%2];" : "=r"(v.x), "=r"(v.y) : "r"(a) : "memory"); return v; }
__device__ __forceinline__ uint32_t lds32(uint32_t a) { uint32_t v; asm volatile("ld.shared.u32 %0, [%1];" : "=r"(v) : "r"(a) : "memory"); return v; }
__device__ __forceinline__ uint32_t lds16(uint32_t a) { uint16_t v; asm volatile("ld.shared.u16 %0, [%1];" : "=h"(v) : "r"(a) : "memory"); return v; }
__device__ __forceinline__ void sts32(uint32_t a, uint32_t v) { asm volatile("st.shared.u32 [%0], %1;" :: "r"(a), "r"(v) : "memory"); }
__device__ __forceinline__ void sts16(uint32_t a, uint32_t v) { asm volatile("st.shared.u16 [%0], %1;" :: "r"(a), "h"((uint16_t)v) : "memory"); }
__device__ __forceinline__ uint32_t atoms_inc(uint32_t a) { uint32_t r; asm volatile("atom.shared.add.u32 %0, [%1], 1;" : "=r"(r) : "r"(a) : "memory"); return r; }
__device__ __forceinline__ void sts128(uint32_t a, uint32_t x, uint32_t y, uint32_t z, uint32_t w) {
    asm volatile("st.shared.v4.u32 [%0], {%1,%2,%3,%4};" :: "r"(a), "r"(x), "r"(y), "r"(z), "r"(w) : "memory");
}
__device__ __forceinline__ void bar_sync(int id, int n)   { asm volatile("bar.sync %0, %1;" :: "r"(id), "r"(n) : "memory"); }
__device__ __forceinline__ void bar_arrive(int id, int n) { asm volatile("bar.arrive %0, %1;" :: "r"(id), "r"(n) : "memory"); }
__device__ __forceinline__ uint32_t clock32() { uint32_t c; asm volatile("mov.u32 %0, %clock;" : "=r"(c)); return c; }
__device__ __forceinline__ void mbar_wait(uint32_t mb) {
    asm volatile("{\n.reg .pred p;\n.reg .u32 i;\nmov.u32 i, 0;\n"
                 "W: mbarrier.try_wait.parity.shared::cta.b64 p, [%0], 0;\n@p bra D;\n"
                 "add.u32 i, i, 1;\nsetp.lt.u32 p, i, 4000000;\n@p bra W;\ntrap;\nD:\n}" :: "r"(mb) : "memory");
}
__device__ __forceinline__ void mbar_wait_all(uint32_t mb) {
    asm volatile("{\n.reg .pred p;\n.reg .u32 i;\nmov.u32 i, 0;\n"
                 "W: mbarrier.test_wait.parity.shared::cta.b64 p, [%0], 0;\nvote.sync.all.pred p, p, 0xffffffff;\n@p bra.uni D;\n"
                 "add.u32 i, i, 1;\nsetp.lt.u32 p, i, 40000000;\n@p bra.uni W;\ntrap;\nD:\n}" :: "r"(mb) : "memory");
}
__device__ __forceinline__ void warp_arrive(uint32_t mb, int lane) {
    __syncwarp();
    if (lane == 0) asm volatile("mbarrier.arrive.shared::cta.b64 _, [%0];" :: "r"(mb) : "memory");
}
__device__ __forceinline__ void tma2d(uint32_t dst, const CUtensorMap* tm, int c0, int c1, uint32_t mb) {
    asm volatile("cp.async.bulk.tensor.2d.shared::cluster.global.mbarrier::complete_tx::bytes [%0], [%1, {%2, %3}], [%4];"
                 :: "r"(dst), "l"(tm), "r"(c0), "r"(c1), "r"(mb) : "memory");
}
__device__ __forceinline__ void load_w(uint32_t dst, const CUtensorMap* tm, uint32_t mb) {
    tma2d(dst, tm, 0, 0, mb);
    tma2d(dst + 16384, tm, 64, 0, mb);
}
__device__ __forceinline__ bool mbar_test(uint32_t mb) {
    uint32_t r;
    asm volatile("{\n.reg .pred p;\nmbarrier.test_wait.parity.shared::cta.b64 p, [%1], 0;\nselp.u32 %0, 1, 0, p;\n}" : "=r"(r) : "r"(mb) : "memory");
    return r;
}
__device__ __forceinline__ uint32_t pack_bf16(float lo, float hi) {
    uint32_t r; asm("cvt.rn.bf16x2.f32 %0, %1, %2;" : "=r"(r) : "f"(hi), "f"(lo)); return r;
}
constexpr float QSCALE = 0.04419417382f;
__device__ __forceinline__ float th(float s) { float r; asm("tanh.approx.f32 %0, %1;" : "=f"(r) : "f"(s)); return r; }
__device__ __forceinline__ uint64_t make_desc(uint32_t addr) {
    return (uint64_t)((addr & 0x3FFFF) >> 4) | ((uint64_t)1 << 16) | ((uint64_t)64 << 32) | ((uint64_t)1 << 62);
}

#define WG_D8(o)  "+f"(d[o]), "+f"(d[o + 1]), "+f"(d[o + 2]), "+f"(d[o + 3]), "+f"(d[o + 4]), "+f"(d[o + 5]), "+f"(d[o + 6]), "+f"(d[o + 7])
__device__ __forceinline__ void wgmma48(float* d, uint64_t a, uint64_t b, uint32_t acc) {
    asm volatile("{\n.reg .pred p;\nsetp.ne.u32 p, %26, 0;\n"
        "wgmma.mma_async.sync.aligned.m64n48k16.f32.bf16.bf16 "
        "{%0,%1,%2,%3,%4,%5,%6,%7,%8,%9,%10,%11,%12,%13,%14,%15,%16,%17,%18,%19,%20,%21,%22,%23}, %24, %25, p, 1, 1, 1, 0;\n}"
        : WG_D8(0), WG_D8(8), WG_D8(16) : "l"(a), "l"(b), "r"(acc) : "memory");
}
__device__ __forceinline__ void wgmma32(float* d, uint64_t a, uint64_t b, uint32_t acc) {
    asm volatile("{\n.reg .pred p;\nsetp.ne.u32 p, %18, 0;\n"
        "wgmma.mma_async.sync.aligned.m64n32k16.f32.bf16.bf16 "
        "{%0,%1,%2,%3,%4,%5,%6,%7,%8,%9,%10,%11,%12,%13,%14,%15}, %16, %17, p, 1, 1, 1, 0;\n}"
        : WG_D8(0), WG_D8(8) : "l"(a), "l"(b), "r"(acc) : "memory");
}
__device__ __forceinline__ void wgmma48r(float* d, const uint4& a, uint64_t b, uint32_t acc) {
    asm volatile("{\n.reg .pred p;\nsetp.ne.u32 p, %29, 0;\n"
        "wgmma.mma_async.sync.aligned.m64n48k16.f32.bf16.bf16 "
        "{%0,%1,%2,%3,%4,%5,%6,%7,%8,%9,%10,%11,%12,%13,%14,%15,%16,%17,%18,%19,%20,%21,%22,%23}, {%24,%25,%26,%27}, %28, p, 1, 1, 0;\n}"
        : WG_D8(0), WG_D8(8), WG_D8(16) : "r"(a.x), "r"(a.y), "r"(a.z), "r"(a.w), "l"(b), "r"(acc) : "memory");
}
__device__ __forceinline__ void wgmma32r(float* d, const uint4& a, uint64_t b, uint32_t acc) {
    asm volatile("{\n.reg .pred p;\nsetp.ne.u32 p, %21, 0;\n"
        "wgmma.mma_async.sync.aligned.m64n32k16.f32.bf16.bf16 "
        "{%0,%1,%2,%3,%4,%5,%6,%7,%8,%9,%10,%11,%12,%13,%14,%15}, {%16,%17,%18,%19}, %20, p, 1, 1, 0;\n}"
        : WG_D8(0), WG_D8(8) : "r"(a.x), "r"(a.y), "r"(a.z), "r"(a.w), "l"(b), "r"(acc) : "memory");
}
__device__ __forceinline__ void stsm4t(uint32_t a, const float* d) {
    asm volatile("stmatrix.sync.aligned.m8n8.x4.trans.shared.b16 [%0], {%1,%2,%3,%4};"
                 :: "r"(a), "r"(pack_bf16(d[0], d[1])), "r"(pack_bf16(d[2], d[3])), "r"(pack_bf16(d[4], d[5])), "r"(pack_bf16(d[6], d[7])) : "memory");
}

__device__ __forceinline__ uint32_t make_entry(uint32_t s, uint32_t dl) { return dl * 16384u + s; }
__device__ __forceinline__ void st_b128(void* p, uint32_t a, uint32_t b, uint32_t c, uint32_t d) {
    asm volatile("{\n.reg .b128 v;\n.reg .b64 lo, hi;\nmov.b64 lo, {%1,%2};\nmov.b64 hi, {%3,%4};\nmov.b128 v, {lo, hi};\n"
                 "st.relaxed.gpu.global.b128 [%0], v;\n}" :: "l"(p), "r"(a), "r"(b), "r"(c), "r"(d) : "memory");
}
__device__ __forceinline__ uint4 ld_b128(const void* p) {
    uint4 w;
    asm volatile("{\n.reg .b128 v;\n.reg .b64 lo, hi;\nld.relaxed.gpu.global.b128 v, [%4];\nmov.b128 {lo, hi}, v;\n"
                 "mov.b64 {%0,%1}, lo;\nmov.b64 {%2,%3}, hi;\n}" : "=r"(w.x), "=r"(w.y), "=r"(w.z), "=r"(w.w) : "l"(p) : "memory");
    return w;
}
__device__ __forceinline__ uint4 ldg128(const void* p) {
    uint4 v; asm volatile("ld.global.nc.v4.u32 {%0,%1,%2,%3}, [%4];" : "=r"(v.x), "=r"(v.y), "=r"(v.z), "=r"(v.w) : "l"(p) : "memory"); return v;
}
template <int K>
__device__ __forceinline__ void insert(const uint32_t (&e)[K], uint32_t trash) {
    uint32_t pos[K];
    #pragma unroll
    for (int k = 0; k < K; k++)
        asm volatile("{\n.reg .pred p;\n.reg .b32 t;\nlop3.b32 t, %2, 0x3000, 0, 0x0c;\nsetp.ne.u32 p, t, 0;\nselp.b32 t, %1, %3, p;\n"
                     "atom.shared.add.u32 %0, [t+%4], 2;\n}" : "=r"(pos[k]) : "r"((e[k] >> 9) & 0xFFC), "r"(e[k]), "r"(trash), "n"(SM_LCNT) : "memory");
    #pragma unroll
    for (int k = 0; k < K; k++)
        asm volatile("{\n.reg .pred p;\n.reg .b32 t;\nlop3.b32 t, %2, 0x3000, 0, 0x0c;\nsetp.ne.u32 p, t, 0;\n@p st.shared.u16 [%0], %1;\n}"
                     :: "r"(SM_SUB + (((e[k] >> 6) & 0x7FE0) | (pos[k] & 30))), "h"((uint16_t)e[k]), "r"(e[k]) : "memory");
}

__device__ __forceinline__ void bin(int2 d2, int2 s2) {
    uint32_t tl0 = __umulhi(d2.x, 56512728u), tl1 = __umulhi(d2.y, 56512728u);
    uint32_t p0 = atoms_inc(SM_CNT + tl0 * 4), p1 = atoms_inc(SM_CNT + tl1 * 4);
    sts32(SM_BOX + tl0 * (BOXPITCH * 4) + (min(p0, 31u) * 33 & 124), make_entry(s2.x, d2.x - tl0 * TILE));
    sts32(SM_BOX + tl1 * (BOXPITCH * 4) + (min(p1, 31u) * 33 & 124), make_entry(s2.y, d2.y - tl1 * TILE));
}
__device__ __forceinline__ uint32_t keep(uint32_t v, int lane) { return __shfl_sync(0xffffffffu, v, lane); }
__device__ __forceinline__ void post(void* p, uint32_t e0, uint32_t e1, uint32_t e2, uint32_t e3, uint32_t e4, uint32_t e5, uint32_t f0, uint32_t f1) {
    st_b128(p, e0 + (e1 << 21), (e1 >> 11) + f0 + (e2 << 10), e3 + (e4 << 21), (e4 >> 11) + f1 + (e5 << 10));
}
template <int N>
__device__ __forceinline__ void q_gemm(int r0, int warp, int lane) {
    float d[N];
    const uint64_t da = make_desc(SM_WQ), db = make_desc(SM_T + r0 * 128);
    asm volatile("wgmma.fence.sync.aligned;" ::: "memory");
    #pragma unroll
    for (int s = 0; s < 16; s++) {
        const int h = s & 1, k = s >> 1;
        const uint64_t a = da + (uint64_t)(h * 1024 + k * 128), b = db + (uint64_t)((k >> 2) * 640 + (k & 3) * 2);
        if (N == 48) wgmma48(d + h * (N / 2), a, b, k != 0); else wgmma32(d + h * (N / 2), a, b, k != 0);
    }
    asm volatile("wgmma.commit_group.sync.aligned;" ::: "memory");
    asm volatile("wgmma.wait_group.sync.aligned 0;" ::: "memory");
    #pragma unroll
    for (int i = 0; i < N; i++) d[i] *= QSCALE;
    bar_sync(1, 128);
    const int r = lane & 7;
    const uint32_t base = SM_T + (r0 + (lane >> 4) * 8 + r) * 128 + (((2 * (warp & 3) + ((lane >> 3) & 1)) ^ r) << 4);
    #pragma unroll
    for (int i = 0; i < N / 8; i++) stsm4t(base + (i / (N / 16)) * 10240 + (i % (N / 16)) * 2048, d + i * 8);
}

template <int N, int R0, int H>
__device__ __forceinline__ void v_gemm(int tid, uint4* __restrict__ out, int rows) {
    constexpr uint32_t so = SM_T + H * 10240 + R0 * 128;
    asm volatile("fence.proxy.async.shared::cta;" ::: "memory");
    mbar_wait(SM_MBV);
    uint4 w[8];
    {
        const uint32_t a = SM_WV + H * 16384 + ((tid & 16) / 2 + (tid & 7)) * 128 + (((((tid >> 4) & 6) + ((tid >> 3) & 1)) ^ (tid & 7)) << 4);
        #pragma unroll
        for (int k = 0; k < 8; k++)
            asm volatile("ldmatrix.sync.aligned.m8n8.x4.trans.shared.b16 {%0,%1,%2,%3}, [%4];"
                         : "=r"(w[k].x), "=r"(w[k].y), "=r"(w[k].z), "=r"(w[k].w) : "r"(a + k * 2048) : "memory");
    }
    bar_sync(N == 48 ? 6 : 7, N * 8);
    float d[N / 2];
    const uint64_t db = make_desc(SM_O + R0 * 128);
    asm volatile("wgmma.fence.sync.aligned;" ::: "memory");
    #pragma unroll
    for (int k = 0; k < 8; k++) {
        const uint64_t b = db + (uint64_t)((k >> 2) * 640 + (k & 3) * 2);
        if (N == 48) wgmma48r(d, w[k], b, k != 0); else wgmma32r(d, w[k], b, k != 0);
    }
    asm volatile("wgmma.commit_group.sync.aligned;" ::: "memory");
    const int r = tid & 7;
    const uint32_t wa = so + ((tid & 16) / 2 + r) * 128 + (((((tid >> 4) & 6) + ((tid >> 3) & 1)) ^ r) << 4);
    const int rr = (tid & 127) >> 3;
    const uint32_t ra = so + rr * 128 + ((r ^ (rr & 7)) << 4);
    out += (R0 + rr) * 16 + H * 8 + r;
    rows -= R0 + rr;
    asm volatile("wgmma.wait_group.sync.aligned 0;" ::: "memory");
    #pragma unroll
    for (int i = 0; i < N / 16; i++) stsm4t(wa + i * 2048, d + i * 8);
    bar_sync((N == 48 ? 8 : 12) + H, 128);
    uint4 v[N / 16];
    #pragma unroll
    for (int i = 0; i < N / 16; i++) v[i] = lds128(ra + i * 2048);
    #pragma unroll
    for (int i = 0; i < N / 16; i++)
        if (rows > i * 16) out[i * 256] = v[i];
}

template <int mode>
__global__ void __launch_bounds__(NTHR, 1)
fg_kernel(const unsigned char* __restrict__ x, const int* __restrict__ src, const int* __restrict__ dst,
          uint4* __restrict__ out, Scratch* __restrict__ scr,
          const unsigned char* __restrict__ wq, const unsigned char* __restrict__ wv,
          const __grid_constant__ CUtensorMap tm_x, const __grid_constant__ CUtensorMap tm_wq, const __grid_constant__ CUtensorMap tm_wv) {
    const int tid = threadIdx.x, cta = blockIdx.x;
    const int e2 = min(cta * (SLICE / 2) + tid, N_EDGES / 2 - 1);
    int2 d2, s2;
    asm volatile("ld.global.v2.u32 {%0,%1}, [%4];\nld.global.v2.u32 {%2,%3}, [%5];"
                 : "=r"(d2.x), "=r"(d2.y), "=r"(s2.x), "=r"(s2.y) : "l"((const int2*)dst + e2), "l"((const int2*)src + e2) : "memory");
    const uint32_t t_start = clock32();
    const int warp = tid >> 5, lane = tid & 31;
    const int g = lane >> 2, t = lane & 3;
    uint32_t q[4][4];
    bool have_q = false;
    uint4 buf[4][2];
    const int slot = g >> 1, l8 = lane & 7, node = warp * 4 + slot;
    uint32_t own = SM_SUB + node * 256 + slot * 8;
    uint64_t xb = (uint64_t)x + l8 * 16 - ((uint64_t)slot << 22);

    auto load_q = [&](int row, int t) {
        const uint32_t trow = SM_T + row * 128;
        #pragma unroll
        for (int L = 0; L < 2; L++) {
            uint4 a = lds128(trow + L * 10240 + ((t ^ (row & 7)) << 4)), b = lds128(trow + L * 10240 + (((4 + t) ^ (row & 7)) << 4));
            q[2 * L][0] = a.x; q[2 * L][1] = b.x; q[2 * L][2] = a.y; q[2 * L][3] = b.y;
            q[2 * L + 1][0] = a.z; q[2 * L + 1][1] = b.z; q[2 * L + 1][2] = a.w; q[2 * L + 1][3] = b.w;
        }
    };
    if (warp == NGRP) {
        if (lane == 0 && (mode & 2)) {
            if (cta < 128) {
                asm volatile("cp.async.bulk.prefetch.L2.global [%0], 256;" :: "l"(wq + cta * 256) : "memory");
                asm volatile("cp.async.bulk.prefetch.L2.global [%0], 256;" :: "l"(wv + cta * 256) : "memory");
            }
            if ((uint32_t)__cvta_generic_to_shared(smem) != SB) __trap();
            asm volatile("prefetch.tensormap [%0];" :: "l"(&tm_x) : "memory");
            asm volatile("prefetch.tensormap [%0];" :: "l"(&tm_wq) : "memory");
            asm volatile("prefetch.tensormap [%0];" :: "l"(&tm_wv) : "memory");
            asm volatile("mbarrier.init.shared::cta.b64 [%0], 1;" :: "r"(SM_MBA) : "memory");
            asm volatile("mbarrier.init.shared::cta.b64 [%0], 1;" :: "r"(SM_MBB) : "memory");
            asm volatile("mbarrier.init.shared::cta.b64 [%0], 1;" :: "r"(SM_MBV) : "memory");
            asm volatile("mbarrier.init.shared::cta.b64 [%0], 4;" :: "r"(SM_MBQ) : "memory");
            asm volatile("mbarrier.init.shared::cta.b64 [%0], 4;" :: "r"(SM_MBQ + 8) : "memory");
            asm volatile("mbarrier.init.shared::cta.b64 [%0], %1;" :: "r"(SM_MBF), "n"(NGRP) : "memory");
            asm volatile("mbarrier.init.shared::cta.b64 [%0], 16;" :: "r"(SM_MBL) : "memory");
            asm volatile("fence.proxy.async.shared::cta;" ::: "memory");
            asm volatile("mbarrier.arrive.expect_tx.shared::cta.b64 _, [%0], %1;" :: "r"(SM_MBA), "r"(32768 + 48 * 256) : "memory");
            asm volatile("mbarrier.arrive.expect_tx.shared::cta.b64 _, [%0], %1;" :: "r"(SM_MBB), "r"(32 * 256) : "memory");
            asm volatile("mbarrier.arrive.expect_tx.shared::cta.b64 _, [%0], %1;" :: "r"(SM_MBV), "r"(32768) : "memory");
        }
        __syncwarp();
        bar_arrive(3, NTHR);
        if (!(mode & 2)) return;
        #pragma unroll
        for (int k = 0; k <= 5; k++) {
            const int tk = k < 5 ? T_X + k * X_STEP : 1 << 30, tp = k ? T_X + (k - 1) * X_STEP : -1;
            if (T_WQ < tk && T_WQ >= tp) {
                while (clock32() - t_start < T_WQ) {}
                if (lane == 0) load_w(SM_WQ, &tm_wq, SM_MBA);
            }
            if (T_WV < tk && T_WV >= tp) {
                while (clock32() - t_start < T_WV) {}
                if (lane == 0) load_w(SM_WV, &tm_wv, SM_MBV);
            }
            if (k < 5) {
                while (clock32() - t_start < tk) {}
                if (lane == 0) {
                    tma2d(SM_T + k * 2048, &tm_x, 0, cta * TILE + k * 16, k < 3 ? SM_MBA : SM_MBB);
                    tma2d(SM_T + 10240 + k * 2048, &tm_x, 64, cta * TILE + k * 16, k < 3 ? SM_MBA : SM_MBB);
                }
            }
        }
        while (clock32() - t_start < T_POLL) {}
        __syncwarp();
        bar_arrive(11, 544);
    } else {
        int2 d3 = make_int2(-1, 0), s3 = make_int2(0, 0);
        if (warp == 18 && cta < NPROD && tid + 32 < SLICE / 2) { d3 = __ldg((const int2*)dst + e2 + 32); s3 = __ldg((const int2*)src + e2 + 32); }
        uint32_t tag = 0;
        if (tid == 0) tag = __ldcg(&scr->epoch[cta]);
        if (tid < (132 + TILE * 8 + 4) / 4) {
            const uint32_t v = tid < 33 ? 0 : (tid - 33) * 4 & 24;
            sts128(SM_CNT + tid * 16, v, v, v, v);
        }
        {
            const uint32_t dm = 7 << 11;
            sts128(SM_BOX + tid * 16, dm, dm, dm, dm);
            if (tid < NCTA * 9 - NGRP * 32) sts128(SM_BOX + (tid + NGRP * 32) * 16, dm, dm, dm, dm);
            sts128(SM_SUB + tid * 16, ~0u, ~0u, ~0u, ~0u);
            sts128(SM_SUB + (tid + NGRP * 32) * 16, ~0u, ~0u, ~0u, ~0u);
            if (tid < FCAP) sts128(SM_FOR + tid * 16, ~0u, ~0u, 0, 0);
        }
        if (lane == 0) {
            #pragma unroll
            for (int k = 0; k < 3; k++) asm volatile("mbarrier.init.shared::cta.b64 [%0], 8;" :: "r"(SM_MBP + warp * 24 + k * 8) : "memory");
        }
        __syncwarp();
        #pragma unroll
        for (int k = 0; k < 8; k++) buf[k >> 1][k & 1] = lds128(SM_BOX + warp * 512);
        own = keep(own, lane);
        xb = (uint64_t)keep(xb >> 32, lane) << 32 | keep(xb, lane);
        const uint32_t bp = keep(SM_BOX + (tid >> 2) * (BOXPITCH * 4) + t * 32, lane), cp = keep(SM_CNT + (tid & ~3), lane);
        const uint32_t trash = keep(lane * 4 - 128, lane);
        uint64_t wp = (uint64_t)(scr->mail + (tid >> 2) * MPITCH + cta * 4 + t), mp = (uint64_t)(scr->mail + cta * MPITCH + tid);
        wp = (uint64_t)keep(wp >> 32, lane) << 32 | keep(wp, lane);
        mp = (uint64_t)keep(mp >> 32, lane) << 32 | keep(mp, lane);
        bar_sync(2, NGRP * 32);

        if (cta < NPROD) bin(d2, s2);
        if (warp == 18 && d3.x >= 0) bin(d3, s3);
        if (tid == 0) sts32(SM_MISC + 16, tag + 1);
        bar_sync(3, NTHR);
        const uint32_t c = lds32(cp);
        uint4 u = lds128(bp);
        uint2 v = lds64(bp + 16);
        tag = lds32(SM_MISC + 16);
        const uint32_t par = tag << 31;
        if (tid < NCTA * 4 && cta < NPROD && (mode & 1)) {
            if (__builtin_expect(c > BOXCAP, 0)) {
                if (c > EXTCAP) u.x = u.y = u.z = u.w = v.x = v.y = 6 << 11;
                else if (t == 3 || (t == 2 && c > BOXCAP + 3)) {
                    const uint32_t a = lds32(bp + (t & 1 ? -72 : 56)), b = lds32(bp + (t & 1 ? -40 : -36));
                    st_b128(scr->ext + ((tid >> 2) * NCTA + cta) * 2 + (t & 1), v.y | (a << 21), (a >> 11) | (b << 10), lds32(bp + (t & 1 ? -8 : -4)), tag);
                    v.y = 6 << 11;
                }
            }
            post((void*)wp, u.x, u.y, u.z, u.w, v.x, v.y, 0x80000000u, par);
        }
        if (!(mode & 2)) return;

        if (warp < 16) {
            uint4 w;
            bar_sync(11, 544);
            w = ld_b128((void*)mp);
            if (__builtin_expect(__any_sync(0xffffffffu, (int)(w.y & ~(w.w ^ par)) >= 0), 0)) {
                bool ok;
                int it = 0;
                do {
                    ok = (int)(w.y & ~(w.w ^ par)) < 0;
                    if (!ok) w = ld_b128((void*)mp);
                } while (!__all_sync(0xffffffffu, ok) && ++it < POLL_LIMIT);
                if ((__ballot_sync(0xffffffffu, !ok) >> (lane & ~3)) & 0xF) w = make_uint4(~0x800u, ~0u, ~0u, ~(0x800u << 10));
            }
            const uint32_t e1 = __funnelshift_r(w.x, w.y, 21), e4 = __funnelshift_r(w.z, w.w, 21);
            insert<6>({w.x, e1, w.y >> 10, w.z, e4, w.w >> 10}, trash);
            const bool more = (w.w & (0x3800 << 10)) == (0x3000 << 10);
            if (__builtin_expect(__any_sync(0xffffffffu, more), 0)) {
                bool ok = !more || (w.x & 0x3800) == 0x3000;
                if (more && ok && t == 0) sts32(SM_RESC + atoms_inc(SM_MISC) * 4, tid >> 2);
                w = make_uint4(~0u, ~0u, ~0u, tag);
                int it = 0;
                do {
                    if (!ok) w = ld_b128(scr->ext + (cta * NCTA + (tid >> 2)) * 2 + (t & 1));
                    ok = w.w == tag;
                } while (!__all_sync(0xffffffffu, ok) && ++it < POLL_LIMIT);
                if (!ok) { w = make_uint4(~0u, ~0u, ~0u, 0); sts32(SM_MISC + 4, 1); }
                insert<4>({w.x, __funnelshift_r(w.x, w.y, 21), w.y >> 10, w.z}, trash);
            }
            warp_arrive(SM_MBL, lane);
            if (warp < 12 && mbar_test(SM_MBQ)) { load_q(node, t); have_q = true; }
            mbar_wait(SM_MBL);
        }
    }
    if (warp >= 16) {
        mbar_wait(SM_MBA);
        q_gemm<48>(0, warp, lane);
        warp_arrive(SM_MBQ, lane);
        mbar_wait(SM_MBB);
        mbar_wait(SM_MBL);
        q_gemm<32>(48, warp, lane);
        warp_arrive(SM_MBQ + 8, lane);
        #pragma unroll
        for (int k = 0; k < 8; k++) buf[k >> 1][k & 1] = make_uint4(0, 0, 0, 0);
    }

    const int wg = warp >> 2;
    {
        uint32_t acc[8];
        const uint64_t x0 = (uint64_t)x + l8 * 16;
        auto fetch = [&](uint2 e, int k) {
            if (k & 1) ldrow<1>(buf[k][0], buf[k][1], k < 2 ? e.x : e.y, xb);
            else       ldrow<0>(buf[k][0], buf[k][1], k < 2 ? e.x : e.y, xb);
        };
        const uint32_t vmask = (g & 1) ? 0x30000000u : 0x3000u;
        float ha, hb;
        auto mark = [&](uint2 e) { ha = (~e.x & vmask) ? 0.5f : 0.f; hb = (~e.y & vmask) ? 0.5f : 0.f; };
        auto clear = [&]() {
            #pragma unroll
            for (int i = 0; i < 8; i++) acc[i] = 0;
        };
        clear();
        uint32_t st = 0, ep = own + 32;
        int cnt = 2, step = 0;
        uint4 c;
        uint32_t c4;
        uint2 mi, e = make_uint2(~0u, ~0u);
        if (warp < NGRP) {
            for (bool again = false;; again = true) {
                e = lds64(own);
                mi = lds64(SM_MISC);
                c = lds128(SM_LCNT + ((own - SM_SUB) >> 8) * 32); c4 = lds32(SM_LCNT + 16 + ((own - SM_SUB) >> 8) * 32);
                if (__builtin_expect(mi.x == 0 || again, 1)) break;
                bar_sync(5, NGRP * 32);
                #pragma unroll 1
                for (int k = 0; k < mi.x; k++) {
                    const int e0 = lds32(SM_RESC + k * 4) * SLICE;
                    #pragma unroll 1
                    for (int i = tid; i < SLICE; i += NGRP * 32) {
                        uint32_t dl = (uint32_t)(__ldg(dst + e0 + i) - cta * TILE);
                        if (dl < TILE) insert<1>({make_entry(__ldg(src + e0 + i), dl)}, 0);
                    }
                }
                bar_sync(5, NGRP * 32);
            }
        }
        auto first = [&]() {
            #pragma unroll
            for (int k = 0; k < 4; k++) fetch(e, k);
            mark(e);
        };
        if (warp < NGRP) first();
        if (warp < NGRP) {
            c.x -= slot * 8; c.y -= slot * 8; c.z -= slot * 8; c.w -= slot * 8; c4 -= slot * 8;
            bool generic = __any_sync(0xffffffffu, max(max(max(c.x, c.y), max(c.z, c.w)), c4) > 32 || mi.y);
            const int o0 = max((int)c.x - 8, 0), o1 = max((int)c.y - 8, 0), o2 = max((int)c.z - 8, 0);
            const int rest = c.y + c.z + c.w + c4 + o0;
            const bool helper = rest <= 24 && !generic;
            const int nch = generic ? 0 : max(rest - 25, 0) >> 3;
            uint32_t k0 = 0;
            if (l8 == 0 && (helper || nch)) asm volatile("atom.shared.add.u32 %0, [%1], %2;" : "=r"(k0) : "r"(SM_MISC + (helper ? 12 : 8)), "r"(helper ? 1 : nch) : "memory");
            k0 = __shfl_sync(0xffffffffu, k0, lane & 24);
            const int k3 = helper ? 0 : 8, o3 = max((int)c.w - k3, 0);
            const int no = generic ? 0 : o0 + o1 + o2 + o3 + max((int)c4 - 8, 0);
            const int nh = no - rest + 24 + k3;
            #pragma unroll 1
            for (int j = 2 * l8; j < no; j += 16) {
                uint32_t a = own - slot * 8 + 8 + j, d = own + 32 + c.y + j;
                if (j >= o0) a += 32 - o0;
                if (j >= o0 + o1) a += 32 - o1;
                if (j >= o0 + o1 + o2) a += 24 + k3 - o2;
                if (j >= o0 + o1 + o2 + o3) a += 40 - k3 - o3;
                uint32_t u = lds16((a & ~31) | ((a + slot * 8) & 31));
                const int h1 = 8 + o1 - c.y, h2 = h1 + 8 + o2 - c.z, h3 = h2 + k3 + o3 - c.w;
                if (j >= h1) d += 24 + c.z - o1;
                if (j >= h2) d += 24 + c.w - o2;
                if (j >= h3) d += 32 + c4 - k3 - o3;
                if (j >= nh) {
                    const uint32_t id = k0 + ((j - nh) >> 3);
                    d = SM_FOR + min(id, (uint32_t)FCAP) * 16 + ((j - nh) & 6);
                    u &= 0x3FFF;
                    sts32((d & ~15) + 8, node);
                }
                sts16(d, u);
            }
            generic |= __any_sync(0xffffffffu, k0 + nch > FCAP);
            warp_arrive(SM_MBF, lane);
            st = helper ? 1 | ((k0 + HW) << 8) : nch ? 2 | (nch << 3) | (min(k0, (uint32_t)FCAP) << 8) : 0;
            if (generic) st |= 128;
            if (!have_q) { mbar_wait(SM_MBQ + (warp < 12 ? 0 : 8)); load_q(node, t); }
        } else {
            mbar_wait(SM_MBF);
            step = 4 + ((min(lds32(SM_MISC + 8), (uint32_t)HW) + 3) >> 2);
            cnt = 0;
            st = 1 | (slot << 8);
            xb = x0;
            const uint2 e = lds64(SM_FOR + slot * 16);
            #pragma unroll
            for (int k = 0; k < 4; k++) fetch(e, k);
            mark(e);
        }
        auto weights = [&](uint32_t& a0, uint32_t& a1) {
            float s[4][4];
            #pragma unroll
            for (int i = 0; i < 4; i++) s[i][0] = s[i][1] = s[i][2] = s[i][3] = 0.f;
            #pragma unroll
            for (int k = 0; k < 4; k++) {
                #pragma unroll
                for (int i = 0; i < 4; i++) {
                    const uint4& v = buf[i][k >> 1];
                    mma(s[i], q[k][0], q[k][1], q[k][2], q[k][3], (k & 1) ? v.z : v.x, (k & 1) ? v.w : v.y);
                }
            }
            const float ta = th((g & 1) ? s[1][0] + s[1][3] : s[0][0] + s[0][3]), tb = th((g & 1) ? s[3][0] + s[3][3] : s[2][0] + s[2][3]);
            const uint32_t pk = pack_bf16(fmaf(ta, ha, ha), fmaf(tb, hb, hb));
            a0 = __shfl_sync(0xffffffffu, pk, 9 * slot); a1 = __shfl_sync(0xffffffffu, pk, 9 * slot + 4);
        };
        auto accumulate = [&](uint32_t a, int k) {
            __nv_bfloat162 w = *(__nv_bfloat162*)&a;
            w = (k & 2) ? __high2bfloat162(w) : __low2bfloat162(w);
            const uint32_t v[8] = {buf[k][0].x, buf[k][0].y, buf[k][0].z, buf[k][0].w, buf[k][1].x, buf[k][1].y, buf[k][1].z, buf[k][1].w};
            #pragma unroll
            for (int i = 0; i < 8; i++) { __nv_bfloat162 r = __hfma2(w, *(const __nv_bfloat162*)&v[i], *(__nv_bfloat162*)&acc[i]); acc[i] = *(uint32_t*)&r; }
        };
        auto flush = [&](int node, int l8) {
            const uint32_t id = (st >> 8) & 0xFF;
            const uint32_t d = (st & 4) ? SM_PART + id * 256 + l8 * 16 : SM_O + node * 128 + ((l8 ^ (node & 7)) << 4);
            sts128(d, acc[0], acc[1], acc[2], acc[3]);
            sts128(d + ((st & 4) ? 128 : 10240), acc[4], acc[5], acc[6], acc[7]);
            if (st & 4) asm volatile("mbarrier.arrive.shared::cta.b64 _, [%0];" :: "r"(SM_MBP + id * 8) : "memory");
        };

        if (step != 4) while (true) {
            #pragma unroll 1
            for (; cnt > 0; cnt--) {
                uint32_t a0, a1;
                const uint2 e = lds64(ep);
                ep += 32;
                weights(a0, a1);
                mark(e);
                #pragma unroll
                for (int k = 0; k < 4; k++) { accumulate((k & 1) ? a1 : a0, k); fetch(e, k); }
            }
            cnt = 1;
            int tid;
            asm volatile("mov.u32 %0, %%tid.x;" : "=r"(tid));
            const int lane = tid & 31, warp = tid >> 5, slot = lane >> 3, l8 = lane & 7, node = tid >> 3;
            const uint32_t own = SM_SUB + node * 256 + slot * 8;
            const uint64_t x0 = (uint64_t)x + l8 * 16;
            if (step == 0) {
                if (tid == 0) scr->epoch[cta] = lds32(SM_MISC + 16);
                mbar_wait(SM_MBF);
                const uint2 tot = lds64(SM_MISC + 8);
                const int id = st >> 8, n = (st >> 3) & 15, lim = min(HW + tot.y, PCAP);
                if (st & 1) {
                    if (id < min((int)tot.x, PCAP)) { ep = SM_FOR + id * 16; xb = x0; }
                    else { ep = own + 160; st &= 128; }
                }
                if (__builtin_expect((st & 2) && id + n > lim, 0)) {
                    const int given = max(lim - id, 0);
                    st = (st & 130) | (given << 3) | (id << 8) | ((min(id + n, FCAP) - id - given) << 20);
                }
                step = 1;
                continue;
            }
            if (step == 1 || step > 4) {
                if (st & 1) {
                    flush(node, l8);
                    if (st & 4) st += 4 << 8;
                    st |= 4;
                    load_q(lds32(SM_FOR + ((st >> 8) & 0xFF) * 16 + 8), lane & 3);
                    clear();
                }
                __syncwarp();
                if (step == 1) {
                    step = 2;
                    ep = own + 128;
                    xb = x0 - ((uint64_t)slot << 22);
                    continue;
                }
                if (step > 5) {
                    step--;
                    ep = SM_FOR + ((st >> 8) + 4) * 16;
                    continue;
                }
                step = 3;
            }
            if (step == 2) {
                if (st & 1) {
                    flush(node, l8);
                    st &= 128;
                    load_q(node, lane & 3);
                    const uint32_t d = SM_O + node * 128 + ((l8 ^ (node & 7)) << 4);
                    const uint4 u = lds128(d), v = lds128(d + 10240);
                    acc[0] = u.x; acc[1] = u.y; acc[2] = u.z; acc[3] = u.w; acc[4] = v.x; acc[5] = v.y; acc[6] = v.z; acc[7] = v.w;
                }
                __syncwarp();
                if (__any_sync(0xffffffffu, st & 2)) {
                    int id = (st >> 8) & 0xFF, n = (st & 2) ? (st >> 3) & 15 : 0;
                    do {
                        mbar_wait_all(n > 0 ? SM_MBP + id * 8 : SM_MBF);
                        if (n > 0) {
                            const uint4 u = lds128(SM_PART + id * 256 + l8 * 16), v = lds128(SM_PART + id * 256 + 128 + l8 * 16);
                            const uint32_t p[8] = {u.x, u.y, u.z, u.w, v.x, v.y, v.z, v.w};
                            #pragma unroll
                            for (int i = 0; i < 8; i++) { __nv_bfloat162 r = __hadd2(*(const __nv_bfloat162*)&p[i], *(__nv_bfloat162*)&acc[i]); acc[i] = *(uint32_t*)&r; }
                        }
                        n--; id++;
                    } while (__any_sync(0xffffffffu, n > 0));
                }
                step = 3;
            }
            if (step == 3) {
                if (__builtin_expect(__any_sync(0xffffffffu, st >> 20), 0)) {
                    ep = own + 160;
                    xb = x0;
                    if (st >> 20) { st -= 1 << 20; ep = SM_FOR + (((st >> 8) & 0xFF) + ((st >> 3) & 15) + (st >> 20)) * 16; }
                    continue;
                }
                uint32_t a0, a1;
                weights(a0, a1);
                #pragma unroll
                for (int k = 0; k < 4; k++) accumulate((k & 1) ? a1 : a0, k);
                flush(node, l8);
                if (__builtin_expect(!(st & 128), 1)) break;
                load_q(node, lane & 3);
                xb = x0;
                clear();
                st = 0;
                step = -1;
            }
            float4* fa = g_facc + (cta * NTHR + tid) * 4;
            #pragma unroll
            for (int i = 0; i < 4; i++) {
                float4 f = st ? fa[i] : make_float4(0.f, 0.f, 0.f, 0.f);
                f.x += __uint_as_float(acc[2 * i] << 16);     f.y += __uint_as_float(acc[2 * i] & 0xFFFF0000u);
                f.z += __uint_as_float(acc[2 * i + 1] << 16); f.w += __uint_as_float(acc[2 * i + 1] & 0xFFFF0000u);
                fa[i] = f;
                acc[2 * i] = pack_bf16(f.x, f.y); acc[2 * i + 1] = pack_bf16(f.z, f.w);
            }
            if (st >= N_EDGES) { st = 0; flush(node, l8); break; }
            clear();
            sts32(own + l8 * 32, ~0u); sts32(own + l8 * 32 + 4, ~0u);
            __syncwarp();
            uint32_t m = 0;
            while (st < N_EDGES && !((m + 0x73737373u) & 0x80808080u)) {
                const uint32_t cc = lane < 16 ? (uint32_t)(__ldg(dst + st + lane) - cta * TILE - warp * 4) : 4;
                uint32_t pos = 0, add = 0;
                #pragma unroll
                for (int j = 0; j < 4; j++) {
                    const uint32_t bm = __ballot_sync(0xffffffffu, cc == j);
                    if (cc == j) pos = ((m >> (8 * j)) & 0xFF) + __popc(bm & ((1u << lane) - 1));
                    add += __popc(bm) << (8 * j);
                }
                if (cc < 4) sts16(SM_SUB + (warp * 4 + cc) * 256 + cc * 8 + (pos >> 2) * 32 + (pos & 3) * 2, __ldg(src + st + lane));
                m += add;
                st += 16;
            }
            __syncwarp();
            cnt = (max(max(m & 0xFF, (m >> 8) & 0xFF), max((m >> 16) & 0xFF, m >> 24)) + 3) >> 2;
            const uint2 e = lds64(own);
            ep = own + 32;
            #pragma unroll
            for (int k = 0; k < 4; k++) fetch(e, k);
            mark(e);
        }
    }

    {
        uint4* o = out + cta * TILE * 16;
        const int rows = min(TILE, N_NODES - cta * TILE);
        if (wg >= 3) {
            if (wg == 3) v_gemm<32, 48, 0>(tid, o, rows);
            else v_gemm<32, 48, 1>(tid, o, rows);
        } else if (wg == 2) {
            asm volatile("fence.proxy.async.shared::cta;" ::: "memory");
            bar_arrive(6, 384);
        } else if (wg == 0) v_gemm<48, 0, 0>(tid, o, rows);
        else v_gemm<48, 0, 1>(tid, o, rows);
    }
}

typedef CUresult (*EncodeFn)(CUtensorMap*, CUtensorMapDataType, cuuint32_t, void*, const cuuint64_t*, const cuuint64_t*,
                             const cuuint32_t*, const cuuint32_t*, CUtensorMapInterleave, CUtensorMapSwizzle,
                             CUtensorMapL2promotion, CUtensorMapFloatOOBfill);

static void encode(EncodeFn fn, CUtensorMap* tm, const void* ptr, int rows, int box_rows) {
    cuuint64_t dims[2] = {128, (cuuint64_t)rows};
    cuuint64_t strides[1] = {256};
    cuuint32_t box[2] = {64, (cuuint32_t)box_rows};
    cuuint32_t es[2] = {1, 1};
    fn(tm, CU_TENSOR_MAP_DATA_TYPE_BFLOAT16, 2, (void*)ptr, dims, strides, box, es, CU_TENSOR_MAP_INTERLEAVE_NONE,
       CU_TENSOR_MAP_SWIZZLE_128B, CU_TENSOR_MAP_L2_PROMOTION_NONE, CU_TENSOR_MAP_FLOAT_OOB_FILL_NONE);
}

}

extern "C" void kernel_launch(void* const* d_in, const int* in_sizes, int n_in, void* d_out, int out_size) {
    using namespace fg;
    static int coresident = -1;
    static EncodeFn enc = nullptr;
    static Scratch* scr = nullptr;
    if (coresident < 0) {
        cudaFuncSetAttribute(fg_kernel<1>, cudaFuncAttributeMaxDynamicSharedMemorySize, SM_ALLOC);
        cudaFuncSetAttribute(fg_kernel<2>, cudaFuncAttributeMaxDynamicSharedMemorySize, SM_ALLOC);
        cudaFuncSetAttribute(fg_kernel<3>, cudaFuncAttributeMaxDynamicSharedMemorySize, SM_ALLOC);
        int dev = 0, sms = 0, occ = 0;
        cudaGetDevice(&dev);
        cudaDeviceGetAttribute(&sms, cudaDevAttrMultiProcessorCount, dev);
        cudaOccupancyMaxActiveBlocksPerMultiprocessor(&occ, fg_kernel<3>, NTHR, SM_ALLOC);
        coresident = (sms * occ >= NCTA) ? 1 : 0;
        cudaDriverEntryPointQueryResult qr;
        cudaGetDriverEntryPoint("cuTensorMapEncodeTiled", (void**)&enc, cudaEnableDefault, &qr);
        cudaGetSymbolAddress((void**)&scr, g_scratch);
    }
    CUtensorMap tx, tq, tv;
    encode(enc, &tx, d_in[0], N_NODES, 16);
    encode(enc, &tq, d_in[3], 128, 128);
    encode(enc, &tv, d_in[4], 128, 128);
    const unsigned char* x = (const unsigned char*)d_in[0];
    const unsigned char* wq = (const unsigned char*)d_in[3];
    const unsigned char* wv = (const unsigned char*)d_in[4];
    const int* src = (const int*)d_in[1];
    const int* dst = (const int*)d_in[2];
    if (coresident) {
        fg_kernel<3><<<NCTA, NTHR, SM_ALLOC, cudaStreamPerThread>>>(x, src, dst, (uint4*)d_out, scr, wq, wv, tx, tq, tv);
    } else {
        fg_kernel<1><<<NCTA, NTHR, SM_ALLOC, cudaStreamPerThread>>>(x, src, dst, (uint4*)d_out, scr, wq, wv, tx, tq, tv);
        fg_kernel<2><<<NCTA, NTHR, SM_ALLOC, cudaStreamPerThread>>>(x, src, dst, (uint4*)d_out, scr, wq, wv, tx, tq, tv);
    }
}
```
